```python
import torch

def _softmax(x, axis=-1):
    return torch.softmax(x, dim=axis)
def _gelu(x):
    return torch.nn.functional.gelu(x, approximate="tanh")
def _silu(x):
    return torch.nn.functional.silu(x)
def _sigmoid(x):
    return torch.sigmoid(x)
def _layernorm(x, axis=-1, eps=1e-5):
    m = x.mean(dim=axis, keepdim=True)
    v = x.var(dim=axis, keepdim=True, unbiased=False)
    return (x - m) / torch.sqrt(v + eps)
def _scatter_add(tgt, idx, src, axis=0):
    return tgt.clone().index_add_(axis, idx, src)
def _segment_sum(src, seg, n):
    out = torch.zeros((n,) + src.shape[1:], dtype=src.dtype)
    return out.index_add_(0, seg, src)
def _pad(x, pw):
    flat = tuple(v for pair in reversed(pw) for v in pair)
    return torch.nn.functional.pad(x, flat)

kernel_name = 'recurrent_scan__linear_kernel_hedgehog__dense_activation_gelu__prompt'

def setup_inputs():

    _w = (lambda a: (lambda t: t.to(torch.bfloat16) if t.is_floating_point() else t)(torch.as_tensor(a)))
    def _A_setup():
        B, S, D, H = 1, 2048, 1024, 32
        Dh = D // H
        return {
            "x": _w((lambda *s: torch.randn(*s, dtype=torch.bfloat16) * 0.05)(B, S, D)),
            "wqkv": _w((lambda *s: torch.randn(*s, dtype=torch.bfloat16) * 0.4)(D, 3 * D)),
            "w_phi": _w((lambda *s: torch.randn(*s, dtype=torch.bfloat16) * 0.4)(H, Dh, Dh) * (Dh ** -0.5)),
            "wo": _w((lambda *s: torch.randn(*s, dtype=torch.bfloat16) * 0.2)(D, D)),
        }
    _A_in = _A_setup()

    def _B_setup():
        B, S, D, F = 1, 2048, 1024, 3584
        return {
            "x": _w((lambda *s: torch.randn(*s, dtype=torch.bfloat16) * 0.05)(B, S, D)),
            "w1": _w((lambda *s: torch.randn(*s, dtype=torch.bfloat16) * 0.4)(D, F) * (D ** -0.5)),
            "b1": _w((lambda *s: torch.randn(*s, dtype=torch.bfloat16) * 12.8)(F) * 0.01),
            "w2": _w((lambda *s: torch.randn(*s, dtype=torch.bfloat16) * 0.1)(F, D) * (F ** -0.5)),
            "b2": _w((lambda *s: torch.randn(*s, dtype=torch.bfloat16) * 0.8)(D) * 0.01),
        }
    _B_in = _B_setup()

    return {
        "A_x": _A_in["x"],
        "A_wqkv": _A_in["wqkv"],
        "A_w_phi": _A_in["w_phi"],
        "A_wo": _A_in["wo"],
        "B_x": _B_in["x"],
        "B_w1": _B_in["w1"],
        "B_b1": _B_in["b1"],
        "B_w2": _B_in["w2"],
        "B_b2": _B_in["b2"],
    }

def reference(A_x, A_wqkv, A_w_phi, A_wo, B_x, B_w1, B_b1, B_w2, B_b2):
    def _A_ref(x, wqkv, w_phi, wo):
        B, S, D = x.shape
        H = 32; Dh = D // H
        qkv = (lambda x, *d: x.permute(*d))((x @ wqkv).reshape(B, S, 3, H, Dh), 2, 0, 3, 1, 4)
        q, k, v = qkv[0], qkv[1], qkv[2]
        pq = torch.einsum("bhsd,hdf->bhsf", q, w_phi)
        pk = torch.einsum("bhsd,hdf->bhsf", k, w_phi)
        phi_q = torch.concatenate([_softmax(pq, axis=-1), _softmax(-pq, axis=-1)], axis=-1)
        phi_k = torch.concatenate([_softmax(pk, axis=-1), _softmax(-pk, axis=-1)], axis=-1)
        kv = torch.einsum("bhsf,bhsd->bhfd", phi_k, v)
        z  = torch.einsum("bhsf->bhf", phi_k)
        num = torch.einsum("bhqf,bhfd->bhqd", phi_q, kv)
        den = torch.einsum("bhqf,bhf->bhq", phi_q, z)[..., None] + 1e-6
        o = num / den
        return (lambda x, *d: x.permute(*d))(o, 0, 2, 1, 3).reshape(B, S, D) @ wo

    def _B_ref(x, w1, b1, w2, b2):
        h = torch.einsum("bsd,df->bsf", x, w1) + b1
        h = _gelu(h)
        return torch.einsum("bsf,fd->bsd", h, w2) + b2

    x = A_x
    xn = _layernorm(x, axis=-1)
    s = _A_ref(xn, A_wqkv, A_w_phi, A_wo)
    g = _silu(_B_ref(xn, B_w1, B_b1, B_w2, B_b2))
    return x + s * g
```

```cpp
#include <cuda_runtime.h>
#include <cuda_bf16.h>
#include <cuda.h>
#include <stdint.h>

namespace {

typedef __nv_bfloat16 bf16;
constexpr int SEQ = 2048, DM = 1024, FF = 3584, NH = 32;
constexpr int NCTA = 128;
#define NWARM 0

__device__ __align__(1024) bf16 g_xn[SEQ * DM];
__device__ __align__(1024) float2 g_stats[SEQ];
__device__ __align__(1024) uint32_t g_csp[2][8 * 16 * 256];
__device__ __align__(1024) bf16 g_h[SEQ * FF];
__device__ __align__(1024) bf16 g_o[SEQ * DM];
__device__ __align__(1024) float g_kv[2][NH * 64 * 32];
__device__ __align__(1024) float g_z[2][NH * 64];
constexpr int FL_TICKET = 0, FL_LN = 1, FL_HA = 17, FL_HB = 33, FL_O = 49, FL_KVP = 65, FL_GRP = 73, FL_NUM = 81;
__device__ __align__(1024) unsigned g_flags[FL_NUM * 32];

struct Params {
  CUtensorMap xn, wqkv2, wqkv1, w1x2, w1h, h, o, w2, wo, wphi, xt, out64;
  const bf16* x;
  const bf16* wqkv;
  const bf16* b1;
  const bf16* b2;
};

constexpr uint32_t RING = 0;
constexpr uint32_t SPARE = 147456;
constexpr uint32_t STG = 163840;
constexpr uint32_t BARS = 229376;
constexpr uint32_t MISC = BARS + 336;
constexpr uint32_t BIAS1 = BARS + 352;
constexpr uint32_t ONES = BARS + 2048;
constexpr uint32_t SMEM_BYTES = BARS + 3072;
constexpr uint32_t CSKV = SPARE + 8192;
constexpr uint32_t PHI = SPARE;
constexpr int B_F3 = 0, B_E3 = 3, B_F4 = 6, B_E4 = 10, B_F5 = 14, B_E5 = 19, B_EP = 24, B_HA = 25, B_HB = 26,
              B_O = 27, B_SF = 28, B_SE = 29, B_WPHI = 30, B_SPARE = 31, B_QOP = 32, B_XT = 33, B_G = 34, B_ED = 35,
              B_KVR = 36, B_CSK = 37, B_LND = 38, B_XN = 39, B_ST = 40;

__device__ __forceinline__ uint32_t smem_u32(const void* p) { return (uint32_t)__cvta_generic_to_shared(p); }
__device__ __forceinline__ void mbar_init(uint32_t bar, uint32_t cnt) {
  asm volatile("mbarrier.init.shared::cta.b64 [%0], %1;" ::"r"(bar), "r"(cnt) : "memory");
}
__device__ __forceinline__ void mbar_expect_tx(uint32_t bar, uint32_t bytes) {
  asm volatile("mbarrier.arrive.expect_tx.shared::cta.b64 _, [%0], %1;" ::"r"(bar), "r"(bytes) : "memory");
}
__device__ __forceinline__ void mbar_arrive(uint32_t bar) {
  asm volatile("mbarrier.arrive.shared::cta.b64 _, [%0];" ::"r"(bar) : "memory");
}
__device__ __forceinline__ void mbar_arrive_cluster(uint32_t bar, uint32_t cta) {
  asm volatile("{\n.reg .b32 ra;\nmapa.shared::cluster.u32 ra, %0, %1;\n"
               "mbarrier.arrive.shared::cluster.b64 _, [ra];\n}" ::"r"(bar), "r"(cta) : "memory");
}
__device__ __forceinline__ bool mbar_test(uint32_t bar, uint32_t parity) {
  uint32_t ok;
  asm volatile("{\n.reg .pred p;\nmbarrier.test_wait.parity.shared::cta.b64 p, [%1], %2;\nselp.u32 %0, 1, 0, p;\n}"
               : "=r"(ok) : "r"(bar), "r"(parity) : "memory");
  return ok;
}
__device__ __forceinline__ void mbar_wait(uint32_t bar, uint32_t parity) {
  asm volatile("{\n.reg .pred p;\n.reg .u32 n;\nmov.u32 n, 0;\n"
               "WAIT_LOOP:\n"
               "mbarrier.try_wait.parity.shared::cta.b64 p, [%0], %1;\n"
               "@p bra WAIT_DONE;\n"
               "add.u32 n, n, 1;\n"
               "setp.lt.u32 p, n, 16777216;\n"
               "@p bra WAIT_LOOP;\n"
               "trap;\n"
               "WAIT_DONE:\n}" ::"r"(bar), "r"(parity) : "memory");
}
__device__ __forceinline__ void mbar_wait_sleep(uint32_t bar, uint32_t parity) {
  mbar_wait(bar, parity);
}
__device__ __forceinline__ void tma_2d(uint32_t dst, const CUtensorMap* m, int x, int y, uint32_t bar) {
  asm volatile("cp.async.bulk.tensor.2d.shared::cluster.global.mbarrier::complete_tx::bytes [%0], [%1, {%3, %4}], [%2];"
               ::"r"(dst), "l"(m), "r"(bar), "r"(x), "r"(y) : "memory");
}
__device__ __forceinline__ void tma_3d_mc(uint32_t dst, const CUtensorMap* m, int x, int y, int z, uint32_t bar) {
  asm volatile("cp.async.bulk.tensor.3d.shared::cluster.global.mbarrier::complete_tx::bytes.multicast::cluster"
               " [%0], [%1, {%3, %4, %5}], [%2], %6;"
               ::"r"(dst), "l"(m), "r"(bar), "r"(x), "r"(y), "r"(z), "h"((uint16_t)3) : "memory");
}
__device__ __forceinline__ void tma_prefetch_3d(const CUtensorMap* m, int x, int y, int z) {
  asm volatile("cp.async.bulk.prefetch.tensor.3d.L2.global.tile [%0, {%1, %2, %3}];"
               ::"l"(m), "r"(x), "r"(y), "r"(z) : "memory");
}
__device__ __forceinline__ void tma_prefetch_2d(const CUtensorMap* m, int x, int y) {
  asm volatile("cp.async.bulk.prefetch.tensor.2d.L2.global.tile [%0, {%1, %2}];" ::"l"(m), "r"(x), "r"(y) : "memory");
}
__device__ __forceinline__ void tma_store_2d(const CUtensorMap* m, uint32_t src, int x, int y) {
  asm volatile("cp.async.bulk.tensor.2d.global.shared::cta.bulk_group [%0, {%2, %3}], [%1];"
               ::"l"(m), "r"(src), "r"(x), "r"(y) : "memory");
}
__device__ __forceinline__ void bulk_reduce_add_f32(void* dst, uint32_t src, uint32_t bytes) {
  asm volatile("cp.reduce.async.bulk.global.shared::cta.bulk_group.add.f32 [%0], [%1], %2;"
               ::"l"(dst), "r"(src), "r"(bytes) : "memory");
}
__device__ __forceinline__ void bulk_commit() { asm volatile("cp.async.bulk.commit_group;" ::: "memory"); }
__device__ __forceinline__ void bulk_wait_all() { asm volatile("cp.async.bulk.wait_group 0;" ::: "memory"); }
__device__ __forceinline__ void bulk_wait_read() { asm volatile("cp.async.bulk.wait_group.read 0;" ::: "memory"); }
__device__ __forceinline__ void fence_async() { asm volatile("fence.proxy.async;" ::: "memory"); }
__device__ __forceinline__ void fence_async_smem() { asm volatile("fence.proxy.async.shared::cta;" ::: "memory"); }
__device__ __forceinline__ void wg_fence() { asm volatile("wgmma.fence.sync.aligned;" ::: "memory"); }
__device__ __forceinline__ void wg_commit() { asm volatile("wgmma.commit_group.sync.aligned;" ::: "memory"); }
template <int N>
__device__ __forceinline__ void wg_wait() { asm volatile("wgmma.wait_group.sync.aligned %0;" ::"n"(N) : "memory"); }
__device__ __forceinline__ void wg_wait0_after(uint32_t dep) {
  asm volatile("{\n.reg .pred p;\nsetp.eq.u32 p, %0, 0xFFFFFFFF;\n@p trap;\nwgmma.wait_group.sync.aligned 0;\n}" ::"r"(dep) : "memory");
}
template <int R>
__device__ __forceinline__ void reg_alloc() { asm volatile("setmaxnreg.inc.sync.aligned.u32 %0;" ::"n"(R)); }
template <int R>
__device__ __forceinline__ void reg_dealloc() { asm volatile("setmaxnreg.dec.sync.aligned.u32 %0;" ::"n"(R)); }
__device__ __forceinline__ void named_sync(int id, int n) { asm volatile("bar.sync %0, %1;" ::"r"(id), "r"(n) : "memory"); }
__device__ __forceinline__ bool elect_one() {
  uint32_t ok;
  asm volatile("{\n.reg .pred p;\nelect.sync _|p, 0xffffffff;\nselp.u32 %0, 1, 0, p;\n}" : "=r"(ok));
  return ok;
}
__device__ __forceinline__ void cluster_arrive() { asm volatile("barrier.cluster.arrive.release.aligned;" ::: "memory"); }
__device__ __forceinline__ void cluster_arrive_relaxed() { asm volatile("barrier.cluster.arrive.relaxed.aligned;" ::: "memory"); }
__device__ __forceinline__ void cluster_wait() { asm volatile("barrier.cluster.wait.acquire.aligned;" ::: "memory"); }
template <int N>
__device__ __forceinline__ void fence_regs(float (&d)[N]) {
#pragma unroll
  for (int i = 0; i < N; i++) asm volatile("" : "+f"(d[i])::"memory");
}
__device__ __forceinline__ uint64_t make_desc(uint32_t addr, uint32_t lbo, uint32_t sbo, uint32_t swz) {
  return (uint64_t)((addr & 0x3FFFF) >> 4) | ((uint64_t)(lbo >> 4) << 16) | ((uint64_t)(sbo >> 4) << 32) |
         ((uint64_t)swz << 62);
}
__device__ __forceinline__ uint64_t desc_add(uint64_t d, uint32_t bytes) {
  return (d & 0xFFFFFFFF00000000ull) | (uint32_t)((uint32_t)d + (bytes >> 4));
}
__device__ __forceinline__ void stsm4(uint32_t addr, uint32_t r0, uint32_t r1, uint32_t r2, uint32_t r3) {
  asm volatile("stmatrix.sync.aligned.m8n8.x4.shared.b16 [%0], {%1, %2, %3, %4};"
               ::"r"(addr), "r"(r0), "r"(r1), "r"(r2), "r"(r3) : "memory");
}
__device__ __forceinline__ void ldsm4(uint32_t addr, uint32_t& r0, uint32_t& r1, uint32_t& r2, uint32_t& r3) {
  asm volatile("ldmatrix.sync.aligned.m8n8.x4.shared.b16 {%0, %1, %2, %3}, [%4];"
               : "=r"(r0), "=r"(r1), "=r"(r2), "=r"(r3) : "r"(addr) : "memory");
}
__device__ __forceinline__ float2 lds64f(uint32_t addr) {
  float2 v;
  asm volatile("ld.shared.v2.f32 {%0, %1}, [%2];" : "=f"(v.x), "=f"(v.y) : "r"(addr) : "memory");
  return v;
}
__device__ __forceinline__ uint2 ld_relaxed_v2(const uint32_t* p) {
  uint2 v;
  asm volatile("ld.relaxed.gpu.global.v2.u32 {%0, %1}, [%2];" : "=r"(v.x), "=r"(v.y) : "l"(p) : "memory");
  return v;
}
__device__ __forceinline__ void st_relaxed_v2(uint32_t* p, uint32_t a, uint32_t b) {
  asm volatile("st.relaxed.gpu.global.v2.u32 [%0], {%1, %2};" ::"l"(p), "r"(a), "r"(b) : "memory");
}
__device__ __forceinline__ void sts64f(uint32_t addr, float a, float b) {
  asm volatile("st.shared.v2.f32 [%0], {%1, %2};" ::"r"(addr), "f"(a), "f"(b) : "memory");
}
__device__ __forceinline__ uint4 lds128(uint32_t addr) {
  uint4 v;
  asm volatile("ld.shared.v4.u32 {%0, %1, %2, %3}, [%4];" : "=r"(v.x), "=r"(v.y), "=r"(v.z), "=r"(v.w) : "r"(addr) : "memory");
  return v;
}
__device__ __forceinline__ void sts32(uint32_t addr, uint32_t a) {
  asm volatile("st.shared.u32 [%0], %1;" ::"r"(addr), "r"(a) : "memory");
}
__device__ __forceinline__ void sts32f(uint32_t addr, float a) {
  asm volatile("st.shared.f32 [%0], %1;" ::"r"(addr), "f"(a) : "memory");
}
__device__ __forceinline__ void sts128(uint32_t addr, uint4 v) {
  asm volatile("st.shared.v4.u32 [%0], {%1, %2, %3, %4};" ::"r"(addr), "r"(v.x), "r"(v.y), "r"(v.z), "r"(v.w) : "memory");
}
__device__ __forceinline__ uint32_t pack2(float lo, float hi) {
  uint32_t r;
  asm("cvt.rn.bf16x2.f32 %0, %1, %2;" : "=r"(r) : "f"(hi), "f"(lo));
  return r;
}
__device__ __forceinline__ float bf_lo(uint32_t v) { return __uint_as_float(v << 16); }
__device__ __forceinline__ float bf_hi(uint32_t v) { return __uint_as_float(v & 0xFFFF0000u); }
__device__ __forceinline__ float bf_round(float v) { return __bfloat162float(__float2bfloat16_rn(v)); }
__device__ __forceinline__ uint32_t badd2(uint32_t a, uint32_t b) {
  uint32_t r;
  asm("add.rn.bf16x2 %0, %1, %2;" : "=r"(r) : "r"(a), "r"(b));
  return r;
}
__device__ __forceinline__ uint32_t bfma2(uint32_t a, uint32_t b, uint32_t c) {
  uint32_t r;
  asm("fma.rn.bf16x2 %0, %1, %2, %3;" : "=r"(r) : "r"(a), "r"(b), "r"(c));
  return r;
}
__device__ __forceinline__ uint32_t bmul2(uint32_t a, uint32_t b) {
  uint32_t r;
  asm("mul.rn.bf16x2 %0, %1, %2;" : "=r"(r) : "r"(a), "r"(b));
  return r;
}
__device__ __forceinline__ uint32_t bmax2(uint32_t a, uint32_t b) {
  uint32_t r;
  asm("max.bf16x2 %0, %1, %2;" : "=r"(r) : "r"(a), "r"(b));
  return r;
}
__device__ __forceinline__ uint32_t bmin2(uint32_t a, uint32_t b) {
  uint32_t r;
  asm("min.bf16x2 %0, %1, %2;" : "=r"(r) : "r"(a), "r"(b));
  return r;
}
__device__ __forceinline__ float ex2(float v) {
  float r;
  asm("ex2.approx.ftz.f32 %0, %1;" : "=f"(r) : "f"(v));
  return r;
}
__device__ __forceinline__ float rcp(float v) {
  float r;
  asm("rcp.approx.ftz.f32 %0, %1;" : "=f"(r) : "f"(v));
  return r;
}
constexpr float LOG2E = 1.4426950408889634f;
__device__ __forceinline__ float gelu_tanh_x2(float u) {
  constexpr float C0 = 0.7978845608028654f, C1 = C0 * 0.044715f;
  float th;
  asm("tanh.approx.f32 %0, %1;" : "=f"(th) : "f"(u * fmaf(u * u, C1, C0)));
  return fmaf(u, th, u);
}
__device__ __forceinline__ float silu(float u) { return u * rcp(1.0f + ex2(-LOG2E * u)); }

__device__ __forceinline__ unsigned ld_acquire(const unsigned* p) {
  unsigned v;
  asm volatile("ld.acquire.gpu.global.u32 %0, [%1];" : "=r"(v) : "l"(p) : "memory");
  return v;
}
__device__ __forceinline__ void flag_signal(int idx) {
  asm volatile("fence.acq_rel.gpu;\nred.relaxed.gpu.global.add.u32 [%0], 1;" ::"l"(g_flags + idx * 32) : "memory");
}
#define FLAG_SLEEP 32
__device__ __forceinline__ void flag_wait(int idx, unsigned target) {
  const unsigned* p = g_flags + idx * 32;
  uint32_t n = 0;
  while ((int)(ld_acquire(p) - target) < 0) {
    if (++n > (1u << 22)) __trap();
    __nanosleep(FLAG_SLEEP);
  }
}
#define PROF_T(slot) do {} while (0)
#define PROF_G(slot) do {} while (0)

template <int TA, int TB>
__device__ __forceinline__ void wgmma_n192(float (&d)[96], uint64_t da, uint64_t db, int sd) {
  asm volatile("{\n.reg .pred p;\nsetp.ne.b32 p, %98, 0;\n"
      "wgmma.mma_async.sync.aligned.m64n192k16.f32.bf16.bf16 "
      "{%0, %1, %2, %3, %4, %5, %6, %7, %8, %9, %10, %11, %12, %13, %14, %15, "
      "%16, %17, %18, %19, %20, %21, %22, %23, %24, %25, %26, %27, %28, %29, %30, %31, "
      "%32, %33, %34, %35, %36, %37, %38, %39, %40, %41, %42, %43, %44, %45, %46, %47, "
      "%48, %49, %50, %51, %52, %53, %54, %55, %56, %57, %58, %59, %60, %61, %62, %63, "
      "%64, %65, %66, %67, %68, %69, %70, %71, %72, %73, %74, %75, %76, %77, %78, %79, "
      "%80, %81, %82, %83, %84, %85, %86, %87, %88, %89, %90, %91, %92, %93, %94, %95}, "
      "%96, %97, p, 1, 1, %99, %100;\n}\n"
      : "+f"(d[0]), "+f"(d[1]), "+f"(d[2]), "+f"(d[3]), "+f"(d[4]), "+f"(d[5]), "+f"(d[6]), "+f"(d[7]),
        "+f"(d[8]), "+f"(d[9]), "+f"(d[10]), "+f"(d[11]), "+f"(d[12]), "+f"(d[13]), "+f"(d[14]), "+f"(d[15]),
        "+f"(d[16]), "+f"(d[17]), "+f"(d[18]), "+f"(d[19]), "+f"(d[20]), "+f"(d[21]), "+f"(d[22]), "+f"(d[23]),
        "+f"(d[24]), "+f"(d[25]), "+f"(d[26]), "+f"(d[27]), "+f"(d[28]), "+f"(d[29]), "+f"(d[30]), "+f"(d[31]),
        "+f"(d[32]), "+f"(d[33]), "+f"(d[34]), "+f"(d[35]), "+f"(d[36]), "+f"(d[37]), "+f"(d[38]), "+f"(d[39]),
        "+f"(d[40]), "+f"(d[41]), "+f"(d[42]), "+f"(d[43]), "+f"(d[44]), "+f"(d[45]), "+f"(d[46]), "+f"(d[47]),
        "+f"(d[48]), "+f"(d[49]), "+f"(d[50]), "+f"(d[51]), "+f"(d[52]), "+f"(d[53]), "+f"(d[54]), "+f"(d[55]),
        "+f"(d[56]), "+f"(d[57]), "+f"(d[58]), "+f"(d[59]), "+f"(d[60]), "+f"(d[61]), "+f"(d[62]), "+f"(d[63]),
        "+f"(d[64]), "+f"(d[65]), "+f"(d[66]), "+f"(d[67]), "+f"(d[68]), "+f"(d[69]), "+f"(d[70]), "+f"(d[71]),
        "+f"(d[72]), "+f"(d[73]), "+f"(d[74]), "+f"(d[75]), "+f"(d[76]), "+f"(d[77]), "+f"(d[78]), "+f"(d[79]),
        "+f"(d[80]), "+f"(d[81]), "+f"(d[82]), "+f"(d[83]), "+f"(d[84]), "+f"(d[85]), "+f"(d[86]), "+f"(d[87]),
        "+f"(d[88]), "+f"(d[89]), "+f"(d[90]), "+f"(d[91]), "+f"(d[92]), "+f"(d[93]), "+f"(d[94]), "+f"(d[95])
      : "l"(da), "l"(db), "r"(sd), "n"(TA), "n"(TB));
}

template <int TA, int TB>
__device__ __forceinline__ void wgmma_n128(float (&d)[64], uint64_t da, uint64_t db, int sd) {
  asm volatile("{\n.reg .pred p;\nsetp.ne.b32 p, %66, 0;\n"
      "wgmma.mma_async.sync.aligned.m64n128k16.f32.bf16.bf16 "
      "{%0, %1, %2, %3, %4, %5, %6, %7, %8, %9, %10, %11, %12, %13, %14, %15, "
      "%16, %17, %18, %19, %20, %21, %22, %23, %24, %25, %26, %27, %28, %29, %30, %31, "
      "%32, %33, %34, %35, %36, %37, %38, %39, %40, %41, %42, %43, %44, %45, %46, %47, "
      "%48, %49, %50, %51, %52, %53, %54, %55, %56, %57, %58, %59, %60, %61, %62, %63}, "
      "%64, %65, p, 1, 1, %67, %68;\n}\n"
      : "+f"(d[0]), "+f"(d[1]), "+f"(d[2]), "+f"(d[3]), "+f"(d[4]), "+f"(d[5]), "+f"(d[6]), "+f"(d[7]),
        "+f"(d[8]), "+f"(d[9]), "+f"(d[10]), "+f"(d[11]), "+f"(d[12]), "+f"(d[13]), "+f"(d[14]), "+f"(d[15]),
        "+f"(d[16]), "+f"(d[17]), "+f"(d[18]), "+f"(d[19]), "+f"(d[20]), "+f"(d[21]), "+f"(d[22]), "+f"(d[23]),
        "+f"(d[24]), "+f"(d[25]), "+f"(d[26]), "+f"(d[27]), "+f"(d[28]), "+f"(d[29]), "+f"(d[30]), "+f"(d[31]),
        "+f"(d[32]), "+f"(d[33]), "+f"(d[34]), "+f"(d[35]), "+f"(d[36]), "+f"(d[37]), "+f"(d[38]), "+f"(d[39]),
        "+f"(d[40]), "+f"(d[41]), "+f"(d[42]), "+f"(d[43]), "+f"(d[44]), "+f"(d[45]), "+f"(d[46]), "+f"(d[47]),
        "+f"(d[48]), "+f"(d[49]), "+f"(d[50]), "+f"(d[51]), "+f"(d[52]), "+f"(d[53]), "+f"(d[54]), "+f"(d[55]),
        "+f"(d[56]), "+f"(d[57]), "+f"(d[58]), "+f"(d[59]), "+f"(d[60]), "+f"(d[61]), "+f"(d[62]), "+f"(d[63])
      : "l"(da), "l"(db), "r"(sd), "n"(TA), "n"(TB));
}

template <int TB, int OFF>
__device__ __forceinline__ void wgmma_rs_n32(float (&d)[64], uint32_t a0, uint32_t a1, uint32_t a2, uint32_t a3,
                                            uint64_t db, int sd) {
  asm volatile("{\n.reg .pred p;\nsetp.ne.b32 p, %21, 0;\n"
      "wgmma.mma_async.sync.aligned.m64n32k16.f32.bf16.bf16 "
      "{%0, %1, %2, %3, %4, %5, %6, %7, %8, %9, %10, %11, %12, %13, %14, %15}, "
      "{%16, %17, %18, %19}, %20, p, 1, 1, %22;\n}\n"
      : "+f"(d[OFF + 0]), "+f"(d[OFF + 1]), "+f"(d[OFF + 2]), "+f"(d[OFF + 3]), "+f"(d[OFF + 4]), "+f"(d[OFF + 5]), "+f"(d[OFF + 6]), "+f"(d[OFF + 7]),
        "+f"(d[OFF + 8]), "+f"(d[OFF + 9]), "+f"(d[OFF + 10]), "+f"(d[OFF + 11]), "+f"(d[OFF + 12]), "+f"(d[OFF + 13]), "+f"(d[OFF + 14]), "+f"(d[OFF + 15])
      : "r"(a0), "r"(a1), "r"(a2), "r"(a3), "l"(db), "r"(sd), "n"(TB));
}

template <int TA, int TB>
__device__ __forceinline__ void wgmma_n40(float (&d)[20], uint64_t da, uint64_t db, int sd) {
  asm volatile("{\n.reg .pred p;\nsetp.ne.b32 p, %22, 0;\n"
      "wgmma.mma_async.sync.aligned.m64n40k16.f32.bf16.bf16 "
      "{%0, %1, %2, %3, %4, %5, %6, %7, %8, %9, %10, %11, %12, %13, %14, %15, "
      "%16, %17, %18, %19}, "
      "%20, %21, p, 1, 1, %23, %24;\n}\n"
      : "+f"(d[0]), "+f"(d[1]), "+f"(d[2]), "+f"(d[3]), "+f"(d[4]), "+f"(d[5]), "+f"(d[6]), "+f"(d[7]),
        "+f"(d[8]), "+f"(d[9]), "+f"(d[10]), "+f"(d[11]), "+f"(d[12]), "+f"(d[13]), "+f"(d[14]), "+f"(d[15]),
        "+f"(d[16]), "+f"(d[17]), "+f"(d[18]), "+f"(d[19])
      : "l"(da), "l"(db), "r"(sd), "n"(TA), "n"(TB));
}

template <int TB>
__device__ __forceinline__ void wgmma_rs_n40(float (&d)[20], uint32_t a0, uint32_t a1, uint32_t a2, uint32_t a3,
                                            uint64_t db, int sd) {
  asm volatile("{\n.reg .pred p;\nsetp.ne.b32 p, %25, 0;\n"
      "wgmma.mma_async.sync.aligned.m64n40k16.f32.bf16.bf16 "
      "{%0, %1, %2, %3, %4, %5, %6, %7, %8, %9, %10, %11, %12, %13, %14, %15, "
      "%16, %17, %18, %19}, "
      "{%20, %21, %22, %23}, %24, p, 1, 1, %26;\n}\n"
      : "+f"(d[0]), "+f"(d[1]), "+f"(d[2]), "+f"(d[3]), "+f"(d[4]), "+f"(d[5]), "+f"(d[6]), "+f"(d[7]),
        "+f"(d[8]), "+f"(d[9]), "+f"(d[10]), "+f"(d[11]), "+f"(d[12]), "+f"(d[13]), "+f"(d[14]), "+f"(d[15]),
        "+f"(d[16]), "+f"(d[17]), "+f"(d[18]), "+f"(d[19])
      : "r"(a0), "r"(a1), "r"(a2), "r"(a3), "l"(db), "r"(sd), "n"(TB));
}

#define EXP_HMAP &p.h
#define EXP_COL(x) (x)
#define EXP_WMAP &p.w2
#define EXP_ROW(x) (x)
#define ALIGN_MASK 12
constexpr int NALIGN = ((ALIGN_MASK >> 0) & 1) + ((ALIGN_MASK >> 1) & 1) + ((ALIGN_MASK >> 2) & 1) + ((ALIGN_MASK >> 3) & 1) +
                       ((ALIGN_MASK >> 4) & 1) + ((ALIGN_MASK >> 5) & 1);
#define PF_SPLIT 8
struct NoHook { __device__ __forceinline__ void operator()(int) const {} };
template <int N, int NA, int NB, int NS, int SBYTES, int ROT, class Hook = NoHook>
__device__ __forceinline__ void mainloop(float (&acc)[NA], float (&acc2)[NB], int nsteps, int& li, uint32_t& ph,
                                         uint32_t sb, int wg, int bar_full, int bar_empty, bool real, Hook hook = Hook()) {
  const int l = threadIdx.x & 127;
  const uint64_t da_base = make_desc(sb + RING + wg * 8192, 16, 1024, 1);
  const uint64_t db_base = make_desc(sb + RING + 16384, 8192, 1024, 1);
  int prev = 0;
#pragma unroll 1
  for (int k = 0; k < nsteps; k++) {
    bool released = k == 0;
    if (!mbar_test(sb + BARS + 8 * (bar_full + li), ph) && real) {
      if (!released) {
        wg_wait<0>();
        if (l < 2) mbar_arrive_cluster(sb + BARS + 8 * (bar_empty + prev), l);
        released = true;
      }
      mbar_wait(sb + BARS + 8 * (bar_full + li), ph);
    }
    int ps = li + ROT;
    if (ps >= NS) ps -= NS;
    const uint64_t da0 = desc_add(da_base, ps * SBYTES), db0 = desc_add(db_base, ps * SBYTES);
    wg_fence();
#pragma unroll
    for (int kk = 0; kk < 4; kk++) {
      const uint64_t da = desc_add(da0, kk * 32);
      const uint64_t db = desc_add(db0, kk * 2048);
      if constexpr (N == 256) {
        wgmma_n128<0, 1>(acc, da, db, (k | kk) != 0);
        wgmma_n128<0, 1>(acc2, da, desc_add(db, 16384), (k | kk) != 0);
      }
      if constexpr (N == 192) wgmma_n192<0, 1>(acc, da, db, (k | kk) != 0);
      if constexpr (N == 128) wgmma_n128<0, 1>(acc, da, db, (k | kk) != 0);
    }
    wg_commit();
    if (!released) {
      wg_wait<1>();
      if (l < 2) mbar_arrive_cluster(sb + BARS + 8 * (bar_empty + prev), l);
    }
    hook(k);
    prev = li;
    if (++li == NS) { li = 0; ph ^= 1; }
  }
  wg_wait<0>();
  if (l < 2) mbar_arrive_cluster(sb + BARS + 8 * (bar_empty + prev), l);
  fence_regs(acc);
  if constexpr (N == 256) fence_regs(acc2);
}

template <int N, int G0>
__device__ __forceinline__ void dump_part(float (&acc)[N / 2], uint32_t sb, int wg) {
  const int lane = threadIdx.x & 31, w = (threadIdx.x >> 5) & 3;
  const int row = wg * 64 + w * 16 + ((lane >> 3) & 1) * 8 + (lane & 7);
  const uint32_t base = sb + STG + row * 128;
  const int hi = lane >> 4;
#pragma unroll
  for (int g = 0; g < N / 8; g += 2) {
    const int cg = g + hi;
    const uint32_t addr = base + ((G0 + g) >> 3) * 16384 + (((cg & 7) ^ (lane & 7)) << 4);
    stsm4(addr, pack2(acc[4 * g], acc[4 * g + 1]), pack2(acc[4 * g + 2], acc[4 * g + 3]),
          pack2(acc[4 * g + 4], acc[4 * g + 5]), pack2(acc[4 * g + 6], acc[4 * g + 7]));
  }
}
__device__ __forceinline__ void normalize_acc(float (&acc)[64], uint32_t cs, float2 st0, float2 st1) {
  const uint32_t a = cs + (threadIdx.x & 3) * 8;
#pragma unroll
  for (int g = 0; g < 16; g++) {
    const float2 c = lds64f(a + g * 32);
    acc[4 * g] = fmaf(acc[4 * g], st0.x, st0.y * c.x);
    acc[4 * g + 1] = fmaf(acc[4 * g + 1], st0.x, st0.y * c.y);
    acc[4 * g + 2] = fmaf(acc[4 * g + 2], st1.x, st1.y * c.x);
    acc[4 * g + 3] = fmaf(acc[4 * g + 3], st1.x, st1.y * c.y);
  }
}
__device__ __forceinline__ void project_acc(const float (&in)[64], float (&acc)[64], uint32_t wphi) {
  uint32_t a[32];
#pragma unroll
  for (int i = 0; i < 32; i++) a[i] = pack2(in[2 * i], in[2 * i + 1]);
  const uint64_t db = make_desc(wphi, 512, 512, 2);
  wg_fence();
  wgmma_rs_n32<1, 0>(acc, a[0], a[1], a[2], a[3], db, 0);
  wgmma_rs_n32<1, 16>(acc, a[8], a[9], a[10], a[11], desc_add(db, 2048), 0);
  wgmma_rs_n32<1, 32>(acc, a[16], a[17], a[18], a[19], desc_add(db, 4096), 0);
  wgmma_rs_n32<1, 48>(acc, a[24], a[25], a[26], a[27], desc_add(db, 6144), 0);
  wgmma_rs_n32<1, 0>(acc, a[4], a[5], a[6], a[7], desc_add(db, 1024), 1);
  wgmma_rs_n32<1, 16>(acc, a[12], a[13], a[14], a[15], desc_add(db, 3072), 1);
  wgmma_rs_n32<1, 32>(acc, a[20], a[21], a[22], a[23], desc_add(db, 5120), 1);
  wgmma_rs_n32<1, 48>(acc, a[28], a[29], a[30], a[31], desc_add(db, 7168), 1);
  wg_commit();
  wg_wait<0>();
  fence_regs(acc);
}
__device__ __forceinline__ void dump_v(float (&acc)[64], uint32_t sb, int wg) {
  const int lane = threadIdx.x & 31, w = (threadIdx.x >> 5) & 3;
  const int row = wg * 64 + w * 16 + ((lane >> 3) & 1) * 8 + (lane & 7);
  const uint32_t base = sb + STG + 32768 + row * 64;
  const int hi = lane >> 4, sw = (row >> 1) & 3;
#pragma unroll
  for (int g = 0; g < 16; g += 2) {
    const uint32_t addr = base + (g >> 2) * 8192 + ((((g + hi) & 3) ^ sw) << 4);
    stsm4(addr, pack2(acc[4 * g], acc[4 * g + 1]), pack2(acc[4 * g + 2], acc[4 * g + 3]),
          pack2(acc[4 * g + 4], acc[4 * g + 5]), pack2(acc[4 * g + 6], acc[4 * g + 7]));
  }
}
__device__ __forceinline__ void dump_done(uint32_t sb) {
  fence_async_smem();
  __syncwarp();
  if ((threadIdx.x & 31) == 0) mbar_arrive(sb + BARS + 8 * B_SF);
}

__device__ __forceinline__ void warp_arrive(uint32_t bar) {
  __syncwarp();
  if ((threadIdx.x & 31) == 0) mbar_arrive(bar);
}

__device__ __forceinline__ void gelu_epilogue(uint32_t sb, int nch, uint32_t bias_s, bf16* dst0, bool real) {
  const int t = threadIdx.x & 127;
  const int cg = t & 7, r0 = t >> 3;
  uint32_t src = sb + STG + r0 * 128 + ((cg ^ (r0 & 7)) << 4);
  bias_s += cg * 16;
  bf16* dst = dst0 + (size_t)r0 * FF + cg * 8;
  uint4 v = lds128(src);
#pragma unroll 1
  for (int c = 0; c < nch; c++) {
    const uint4 bias = lds128(bias_s + c * 128);
#pragma unroll 2
    for (int i = 0; i < 8; i++) {
      const uint32_t u0 = badd2(v.x, bias.x), u1 = badd2(v.y, bias.y), u2 = badd2(v.z, bias.z), u3 = badd2(v.w, bias.w);
      src += 2048;
      v = lds128(src);
      uint4 o;
      o.x = pack2(gelu_tanh_x2(bf_lo(u0)), gelu_tanh_x2(bf_hi(u0)));
      o.y = pack2(gelu_tanh_x2(bf_lo(u1)), gelu_tanh_x2(bf_hi(u1)));
      o.z = pack2(gelu_tanh_x2(bf_lo(u2)), gelu_tanh_x2(bf_hi(u2)));
      o.w = pack2(gelu_tanh_x2(bf_lo(u3)), gelu_tanh_x2(bf_hi(u3)));
      if (real) *reinterpret_cast<uint4*>(dst + (size_t)i * 16 * FF + c * 64) = o;
    }
  }
}

__device__ __forceinline__ void kv_colsum_load(uint4 (&v)[16], const bf16* wq) {
  const int t = threadIdx.x & 127;
  const int grp = (t & 63) >> 2, sl = t & 3;
  const bf16* p = wq + (size_t)(sl * 16) * (3 * DM) + (t < 64 ? DM : 2 * DM) + grp * 8;
#pragma unroll
  for (int i = 0; i < 16; i++) v[i] = __ldg(reinterpret_cast<const uint4*>(p + (size_t)i * (3 * DM)));
}
__device__ __forceinline__ void kv_colsum_publish(const uint4 (&v)[16], uint32_t* part, int m, bool real) {
  const int t = threadIdx.x & 127;
  {
    const int sl = t & 3;
    float s[8] = {0.f, 0.f, 0.f, 0.f, 0.f, 0.f, 0.f, 0.f};
#pragma unroll
    for (int i = 0; i < 16; i++) {
      s[0] += bf_lo(v[i].x); s[1] += bf_hi(v[i].x); s[2] += bf_lo(v[i].y); s[3] += bf_hi(v[i].y);
      s[4] += bf_lo(v[i].z); s[5] += bf_hi(v[i].z); s[6] += bf_lo(v[i].w); s[7] += bf_hi(v[i].w);
    }
#pragma unroll
    for (int e = 0; e < 8; e++) {
      s[e] += __shfl_xor_sync(0xffffffffu, s[e], 1);
      s[e] += __shfl_xor_sync(0xffffffffu, s[e], 2);
    }
    const float a = sl == 0 ? s[0] : sl == 1 ? s[2] : sl == 2 ? s[4] : s[6];
    const float b = sl == 0 ? s[1] : sl == 1 ? s[3] : sl == 2 ? s[5] : s[7];
    if (real) st_relaxed_v2(part + m * 256 + (t >> 2) * 8 + sl * 2, ~__float_as_uint(a), ~__float_as_uint(b));
  }
}
__device__ __forceinline__ void kv_colsum_gather(uint32_t sb, const uint32_t* part, bool real) {
  const int t = threadIdx.x & 127;
  uint2 u[16];
  for (uint32_t n = 0;; n++) {
#pragma unroll
    for (int i = 0; i < 16; i++) u[i] = ld_relaxed_v2(part + i * 256 + t * 2);
    bool ok = true;
#pragma unroll
    for (int i = 0; i < 16; i++) ok = ok && u[i].x != 0 && u[i].y != 0;
    if (ok || !real) break;
    if (n > (1u << 18)) __trap();
  }
  float a = 0.f, b = 0.f;
#pragma unroll
  for (int i = 0; i < 16; i++) {
    a += __uint_as_float(~u[i].x);
    b += __uint_as_float(~u[i].y);
  }
  sts64f(sb + CSKV + t * 8, a, b);
}

__device__ __forceinline__ void dual_softmax2(const uint32_t (&p)[2][8], uint32_t (&pos)[2][8], uint32_t (&neg)[2][8]) {
  uint32_t mm[4];
#pragma unroll
  for (int q = 0; q < 4; q++) {
    const uint32_t(&v)[8] = p[q >> 1];
    const int r = q & 1;
    const uint32_t mx2 = bmax2(bmax2(v[r], v[2 + r]), bmax2(v[4 + r], v[6 + r]));
    const uint32_t mn2 = bmin2(bmin2(v[r], v[2 + r]), bmin2(v[4 + r], v[6 + r])) ^ 0x80008000u;
    mm[q] = bmax2(__byte_perm(mx2, mn2, 0x5410), __byte_perm(mx2, mn2, 0x7632));
  }
#pragma unroll
  for (int o = 1; o <= 2; o <<= 1) {
    uint32_t t[4];
#pragma unroll
    for (int q = 0; q < 4; q++) t[q] = __shfl_xor_sync(0xffffffffu, mm[q], o);
#pragma unroll
    for (int q = 0; q < 4; q++) mm[q] = bmax2(mm[q], t[q]);
  }
  float ep[4][8], en[4][8], sp[4], sn[4];
#pragma unroll
  for (int q = 0; q < 4; q++) {
    const float mxl = -LOG2E * bf_lo(mm[q]), mnl = -LOG2E * bf_hi(mm[q]);
#pragma unroll
    for (int g = 0; g < 4; g++) {
      const uint32_t w = p[q >> 1][2 * g + (q & 1)];
      const float v0 = bf_lo(w), v1 = bf_hi(w);
      ep[q][2 * g] = ex2(fmaf(v0, LOG2E, mxl));
      ep[q][2 * g + 1] = ex2(fmaf(v1, LOG2E, mxl));
      en[q][2 * g] = ex2(fmaf(v0, -LOG2E, mnl));
      en[q][2 * g + 1] = ex2(fmaf(v1, -LOG2E, mnl));
    }
    sp[q] = ((ep[q][0] + ep[q][1]) + (ep[q][2] + ep[q][3])) + ((ep[q][4] + ep[q][5]) + (ep[q][6] + ep[q][7]));
    sn[q] = ((en[q][0] + en[q][1]) + (en[q][2] + en[q][3])) + ((en[q][4] + en[q][5]) + (en[q][6] + en[q][7]));
  }
#pragma unroll
  for (int o = 1; o <= 2; o <<= 1) {
    float a[4], b[4];
#pragma unroll
    for (int q = 0; q < 4; q++) { a[q] = __shfl_xor_sync(0xffffffffu, sp[q], o); b[q] = __shfl_xor_sync(0xffffffffu, sn[q], o); }
#pragma unroll
    for (int q = 0; q < 4; q++) { sp[q] += a[q]; sn[q] += b[q]; }
  }
#pragma unroll
  for (int q = 0; q < 4; q++) {
    const float ip = rcp(sp[q]), in = rcp(sn[q]);
#pragma unroll
    for (int g = 0; g < 4; g++) {
      pos[q >> 1][2 * g + (q & 1)] = pack2(ep[q][2 * g] * ip, ep[q][2 * g + 1] * ip);
      neg[q >> 1][2 * g + (q & 1)] = pack2(en[q][2 * g] * in, en[q][2 * g + 1] * in);
    }
  }
}

__device__ __forceinline__ void load_logits(uint32_t sb, int h, uint32_t (&p0)[8], uint32_t (&p1)[8]) {
  const int lane = threadIdx.x & 31, w = (threadIdx.x >> 5) & 3;
  const int srow = w * 16 + ((lane >> 3) & 1) * 8 + (lane & 7);
  const int hi = lane >> 4;
  const uint32_t base = sb + STG + (h >> 1) * 16384 + srow * 128;
  const uint32_t o0 = (((h & 1) * 4 + 0 + hi) ^ (lane & 7)) << 4, o1 = (((h & 1) * 4 + 2 + hi) ^ (lane & 7)) << 4;
  ldsm4(base + o0, p0[0], p0[1], p0[2], p0[3]);
  ldsm4(base + o1, p0[4], p0[5], p0[6], p0[7]);
  ldsm4(base + 8192 + o0, p1[0], p1[1], p1[2], p1[3]);
  ldsm4(base + 8192 + o1, p1[4], p1[5], p1[6], p1[7]);
}

__device__ __forceinline__ void kv_stage(uint32_t sb, int head, const float (&kv)[20]) {
  const int t = threadIdx.x & 127, lane = t & 31;
  const uint32_t dst = sb + STG + 32768 + head * 8192 + t * 16;
#pragma unroll
  for (int i = 0; i < 4; i++)
    sts128(dst + i * 2048, make_uint4(__float_as_uint(kv[4 * i]), __float_as_uint(kv[4 * i + 1]),
                                      __float_as_uint(kv[4 * i + 2]), __float_as_uint(kv[4 * i + 3])));
  if ((lane & 3) == 0) {
    const int f = (t >> 5) * 16 + (lane >> 2);
    sts32f(sb + STG + head * 256 + f * 4, kv[16]);
    sts32f(sb + STG + head * 256 + f * 4 + 32, kv[18]);
  }
}

template <int SGN>
__device__ __forceinline__ void row_exp(const uint32_t (&p)[16], float m, float (&e)[32]) {
  const float ml = -LOG2E * m;
#pragma unroll
  for (int i = 0; i < 16; i++) {
    e[2 * i] = ex2(fmaf(bf_lo(p[i]), SGN * LOG2E, ml));
    e[2 * i + 1] = ex2(fmaf(bf_hi(p[i]), SGN * LOG2E, ml));
  }
}
__device__ __forceinline__ void row_norm(const float (&e)[32], uint32_t (&o)[16]) {
  float s[4];
#pragma unroll
  for (int q = 0; q < 4; q++)
    s[q] = ((e[8 * q] + e[8 * q + 1]) + (e[8 * q + 2] + e[8 * q + 3])) + ((e[8 * q + 4] + e[8 * q + 5]) + (e[8 * q + 6] + e[8 * q + 7]));
  const float inv = rcp((s[0] + s[1]) + (s[2] + s[3]));
#pragma unroll
  for (int i = 0; i < 16; i++) o[i] = pack2(e[2 * i] * inv, e[2 * i + 1] * inv);
}

__device__ __forceinline__ void kv_epilogue(uint32_t sb, int nheads) {
  const int t = threadIdx.x & 127;
  const uint64_t d_phi = make_desc(sb + PHI, 8192, 1024, 1);
  float kv[20];
  const uint32_t phi_row = sb + PHI + t * 128;
#pragma unroll 1
  for (int h = 0; h < nheads; h++) {
    uint32_t pos[16], neg[16], p[16];
    const uint32_t src = sb + STG + (h >> 1) * 16384 + t * 128;
#pragma unroll
    for (int c = 0; c < 4; c++) {
      const uint4 v = lds128(src + ((((h & 1) * 4 + c) ^ (t & 7)) << 4));
      p[4 * c] = v.x; p[4 * c + 1] = v.y; p[4 * c + 2] = v.z; p[4 * c + 3] = v.w;
    }
    uint32_t mx = p[0], mn = p[0];
#pragma unroll
    for (int i = 1; i < 16; i++) { mx = bmax2(mx, p[i]); mn = bmin2(mn, p[i]); }
    float e[32];
    row_exp<1>(p, fmaxf(bf_lo(mx), bf_hi(mx)), e);
    row_norm(e, pos);
    row_exp<-1>(p, -fminf(bf_lo(mn), bf_hi(mn)), e);
    row_norm(e, neg);
    uint32_t dep = 0;
#pragma unroll
    for (int i = 0; i < 16; i++) dep ^= pos[i] ^ neg[i];
    wg_wait0_after(dep);
    fence_regs(kv);
    named_sync(1, 128);
#pragma unroll
    for (int c = 0; c < 4; c++) {
      sts128(phi_row + ((c ^ (t & 7)) << 4), make_uint4(pos[4 * c], pos[4 * c + 1], pos[4 * c + 2], pos[4 * c + 3]));
      sts128(phi_row + (((4 + c) ^ (t & 7)) << 4), make_uint4(neg[4 * c], neg[4 * c + 1], neg[4 * c + 2], neg[4 * c + 3]));
    }
    if (h > 0) kv_stage(sb, h - 1, kv);
    fence_async_smem();
    named_sync(1, 128);
    wg_fence();
#pragma unroll
    for (int ks = 0; ks < 8; ks++) {
      const uint32_t vs = sb + STG + 32768 + h * 8192 + ks * 1024;
      wgmma_n40<1, 1>(kv, desc_add(d_phi, ks * 2048), make_desc(vs, sb + ONES - vs, 512, 2), ks);
    }
    wg_commit();
  }
  wg_wait<0>();
  fence_regs(kv);
  named_sync(1, 128);
  kv_stage(sb, 3, kv);
  fence_async_smem();
}

__device__ __forceinline__ void q_operands(uint32_t sb, const float* kvs, const float* zs) {
  const int t = threadIdx.x & 127, lane = t & 31, w = t >> 5;
  float4 v[16];
#pragma unroll
  for (int i = 0; i < 16; i++) v[i] = __ldcg(reinterpret_cast<const float4*>(kvs) + i * 128 + t);
  const float2 z = __ldcg(reinterpret_cast<const float2*>(zs + w * 64) + lane);
  const int f0 = w * 16 + (lane >> 2);
#pragma unroll
  for (int i = 0; i < 16; i++) {
    const int h = i >> 2, g = i & 3;
    const uint32_t a = sb + STG + 32768 + h * 4096 + f0 * 64 + ((g ^ ((f0 >> 1) & 3)) << 4) + (lane & 3) * 4;
    sts32(a, pack2(v[i].x, v[i].y));
    sts32(a + 512, pack2(v[i].z, v[i].w));
  }
  const uint32_t z0 = pack2(z.x, z.x), z1 = pack2(z.y, z.y);
  const uint32_t zo = sb + STG + 57344 + lane * 128 + ((w ^ (lane & 3)) << 4);
  sts128(zo, make_uint4(z0, z0, z0, z0));
  sts128(zo + 64, make_uint4(z1, z1, z1, z1));
  fence_async_smem();
}

__device__ __forceinline__ void q_epilogue(uint32_t sb, int nheads) {
  const int t = threadIdx.x & 127, lane = t & 31, w = t >> 5;
  const int srow = w * 16 + ((lane >> 3) & 1) * 8 + (lane & 7);
  const int hi = lane >> 4;
  const uint32_t img0 = sb + STG + 32768, zt = sb + STG + 57344;
#pragma unroll 1
  for (int h = 0; h < nheads; h++) {
    uint32_t p[2][8], pos[2][8], neg[2][8];
    load_logits(sb, h, p[0], p[1]);
    dual_softmax2(p, pos, neg);
    const uint32_t img = img0 + h * 4096;
    const uint64_t d_kv = make_desc(img, zt + h * 16 - img, 512, 2);
    float num[2][20];
    wg_fence();
#pragma unroll
    for (int half = 0; half < 2; half++) {
#pragma unroll
      for (int ks = 0; ks < 2; ks++)
        wgmma_rs_n40<1>(num[half], pos[half][4 * ks], pos[half][4 * ks + 1], pos[half][4 * ks + 2], pos[half][4 * ks + 3],
                        desc_add(d_kv, ks * 1024), ks);
#pragma unroll
      for (int ks = 0; ks < 2; ks++)
        wgmma_rs_n40<1>(num[half], neg[half][4 * ks], neg[half][4 * ks + 1], neg[half][4 * ks + 2], neg[half][4 * ks + 3],
                        desc_add(d_kv, (2 + ks) * 1024), 1);
    }
    wg_commit();
    wg_wait<0>();
    const uint32_t dst = sb + STG + (h >> 1) * 16384 + srow * 128;
#pragma unroll
    for (int half = 0; half < 2; half++) {
      fence_regs(num[half]);
      const float(&nm)[20] = num[half];
      const float i0 = 1.0f / bf_round(bf_round(nm[16]) + 1e-6f), i1 = 1.0f / bf_round(bf_round(nm[18]) + 1e-6f);
      uint32_t o[8];
#pragma unroll
      for (int g = 0; g < 4; g++) {
        const uint32_t n0 = pack2(nm[4 * g], nm[4 * g + 1]), n1 = pack2(nm[4 * g + 2], nm[4 * g + 3]);
        o[2 * g] = pack2(bf_lo(n0) * i0, bf_hi(n0) * i0);
        o[2 * g + 1] = pack2(bf_lo(n1) * i1, bf_hi(n1) * i1);
      }
      stsm4(dst + half * 8192 + ((((h & 1) * 4 + 0 + hi) ^ (lane & 7)) << 4), o[0], o[1], o[2], o[3]);
      stsm4(dst + half * 8192 + ((((h & 1) * 4 + 2 + hi) ^ (lane & 7)) << 4), o[4], o[5], o[6], o[7]);
    }
  }
}

__device__ __forceinline__ void gate_epilogue(uint32_t sb, uint4 bias0, uint4 bias1) {
  const int t = threadIdx.x & 127;
  const int cg = t & 7, r0 = t >> 3;
  uint32_t src = sb + STG + r0 * 128 + ((cg ^ (r0 & 7)) << 4);
#pragma unroll 1
  for (int c = 0; c < 2; c++) {
    const uint4 bias = c == 0 ? bias0 : bias1;
#pragma unroll 2
    for (int i = 0; i < 8; i++) {
      const uint4 v = lds128(src);
      const uint32_t u0 = bfma2(v.x, 0x3F003F00u, bias.x), u1 = bfma2(v.y, 0x3F003F00u, bias.y),
                     u2 = bfma2(v.z, 0x3F003F00u, bias.z), u3 = bfma2(v.w, 0x3F003F00u, bias.w);
      uint4 o;
      o.x = pack2(silu(bf_lo(u0)), silu(bf_hi(u0)));
      o.y = pack2(silu(bf_lo(u1)), silu(bf_hi(u1)));
      o.z = pack2(silu(bf_lo(u2)), silu(bf_hi(u2)));
      o.w = pack2(silu(bf_lo(u3)), silu(bf_hi(u3)));
      sts128(src, o);
      src += 2048;
    }
  }
}

template <int NR>
__device__ __forceinline__ void ln_rows(uint4 (&xv)[NR][4], int xrow, bool real) {
  const int lane = threadIdx.x & 31;
  float s[NR], q[NR];
  auto repack = [&]() {
#pragma unroll
    for (int r = 0; r < NR; r++)
#pragma unroll
      for (int i = 0; i < 4; i++)
        asm volatile("" : "+r"(xv[r][i].x), "+r"(xv[r][i].y), "+r"(xv[r][i].z), "+r"(xv[r][i].w));
  };
#pragma unroll
  for (int r = 0; r < NR; r++) {
    float a = 0.f, b = 0.f;
#pragma unroll
    for (int i = 0; i < 4; i++) {
      a += (bf_lo(xv[r][i].x) + bf_hi(xv[r][i].x)) + (bf_lo(xv[r][i].y) + bf_hi(xv[r][i].y));
      b += (bf_lo(xv[r][i].z) + bf_hi(xv[r][i].z)) + (bf_lo(xv[r][i].w) + bf_hi(xv[r][i].w));
    }
    s[r] = a + b;
  }
#pragma unroll
  for (int o = 16; o > 0; o >>= 1) {
    float t[NR];
#pragma unroll
    for (int r = 0; r < NR; r++) t[r] = __shfl_xor_sync(0xffffffffu, s[r], o);
#pragma unroll
    for (int r = 0; r < NR; r++) s[r] += t[r];
  }
  repack();
#pragma unroll
  for (int r = 0; r < NR; r++) {
    s[r] *= (1.0f / DM);
    float a = 0.f, b = 0.f;
#pragma unroll
    for (int i = 0; i < 4; i++) {
      const uint32_t w[4] = {xv[r][i].x, xv[r][i].y, xv[r][i].z, xv[r][i].w};
#pragma unroll
      for (int e = 0; e < 4; e++) {
        const float d0 = bf_lo(w[e]) - s[r], d1 = bf_hi(w[e]) - s[r];
        a = fmaf(d0, d0, a);
        b = fmaf(d1, d1, b);
      }
    }
    q[r] = a + b;
  }
#pragma unroll
  for (int o = 16; o > 0; o >>= 1) {
    float t[NR];
#pragma unroll
    for (int r = 0; r < NR; r++) t[r] = __shfl_xor_sync(0xffffffffu, q[r], o);
#pragma unroll
    for (int r = 0; r < NR; r++) q[r] += t[r];
  }
  repack();
#pragma unroll
  for (int r = 0; r < NR; r++) {
    const float mb = bf_round(s[r]);
    const float sd = bf_round(sqrtf(bf_round(bf_round(q[r] * (1.0f / DM)) + 1e-5f)));
    const float inv = 1.0f / sd;
    if (lane == 0 && real) g_stats[xrow + r] = make_float2(inv, -mb * inv);
#pragma unroll
    for (int i = 0; i < 4; i++) {
      const uint32_t w[4] = {xv[r][i].x, xv[r][i].y, xv[r][i].z, xv[r][i].w};
      uint32_t o[4];
#pragma unroll
      for (int e = 0; e < 4; e++) {
        const uint32_t d = pack2(bf_lo(w[e]) - mb, bf_hi(w[e]) - mb);
        o[e] = pack2(bf_lo(d) * inv, bf_hi(d) * inv);
      }
      if (real) *reinterpret_cast<uint4*>(g_xn + (size_t)(xrow + r) * DM + i * 256 + lane * 8) = make_uint4(o[0], o[1], o[2], o[3]);
    }
  }
}

__global__ void __cluster_dims__(2, 1, 1) __launch_bounds__(512, 1) hedgehog_mlp_fused(const __grid_constant__ Params p) {
  extern __shared__ __align__(1024) uint8_t smem[];
  const uint32_t sb = smem_u32(smem);
  const int tid = threadIdx.x, warp = tid >> 5, lane = tid & 31;
  const int rank = blockIdx.x & 1, cl = blockIdx.x >> 1;
  int unit, k8;
  if (cl >= 64) { unit = 0; k8 = 0; }
  else if (cl < 4) { unit = 7; k8 = 4 + cl; }
  else if (cl < 36) { const int q = (cl - 4) & 7; k8 = (cl - 4) >> 3; unit = q == 0 ? 0 : (q == 1 ? 7 : q - 1); }
  else { k8 = 4 + (cl - 36) / 7; unit = (cl - 36) % 7; }
  const int j = k8, m = unit * 2 + rank;
  const bool real = blockIdx.x < NCTA;
  auto bar = [&](int i) { return sb + BARS + 8 * i; };

  if (tid == 0) { PROF_G(0); PROF_T(1); }
  uint4 xv[2][4];
  const int xrow = m * 128 + j * 16 + (warp < 8 ? warp : 8 + (warp & 3) * 2);
  if (warp < 12) {
#pragma unroll
    for (int i = 0; i < 4; i++) xv[0][i] = __ldg(reinterpret_cast<const uint4*>(p.x + (size_t)xrow * DM + i * 256 + lane * 8));
  }
  if (warp >= 8 && warp < 12) {
#pragma unroll
    for (int i = 0; i < 4; i++) xv[1][i] = __ldg(reinterpret_cast<const uint4*>(p.x + (size_t)(xrow + 1) * DM + i * 256 + lane * 8));
  }
  unsigned ticket = 0;
  if (tid == 480 && real) ticket = atomicAdd(g_flags + FL_TICKET * 32, 1u);
  if (warp == 12 && elect_one()) {
    if (sb & 1023) __trap();
    for (int s = 0; s < 3; s++) { mbar_init(bar(B_F3 + s), 1); mbar_init(bar(B_E3 + s), 4); }
    for (int s = 0; s < 4; s++) { mbar_init(bar(B_F4 + s), 1); mbar_init(bar(B_E4 + s), 4); }
    for (int s = 0; s < 5; s++) { mbar_init(bar(B_F5 + s), 1); mbar_init(bar(B_E5 + s), 4); }
    mbar_init(bar(B_SF), 8);
    mbar_init(bar(B_SE), 4);
    mbar_init(bar(B_ED), 4);
    mbar_init(bar(B_WPHI), 1);
    mbar_init(bar(B_SPARE), 8);
    mbar_init(bar(B_QOP), 1);
    mbar_init(bar(B_XT), 1);
    mbar_init(bar(B_G), 4);
    mbar_init(bar(B_KVR), 1);
    mbar_init(bar(B_EP), 1);
    mbar_init(bar(B_CSK), 4);
    mbar_init(bar(B_LND), 12);
    mbar_init(bar(B_XN), 1);
    mbar_init(bar(B_ST), 1);
    mbar_init(bar(B_HA), 1);
    mbar_init(bar(B_HB), 1);
    mbar_init(bar(B_O), 1);
    asm volatile("fence.mbarrier_init.release.cluster;" ::: "memory");
    for (int s = 0; s < 3 && real; s++) {
      mbar_expect_tx(bar(B_F3 + s), 49152);
      tma_2d(sb + RING + s * 49152, &p.xt, s * 64, m * 128, bar(B_F3 + s));
    }
  }
  __syncwarp();
  cluster_arrive_relaxed();
  if (warp == 12) {
    cluster_wait();
    if (real && elect_one()) {
      for (int s = 0; s < 3; s++)
        tma_3d_mc(sb + RING + s * 49152 + 16384 + rank * 16384, &p.wqkv2, 0, s * 64, 16 + 16 * rank + 2 * j, bar(B_F3 + s));
      if (m >= 3 && m < PF_SPLIT) {
        tma_prefetch_3d(&p.wqkv2, 0, m * 64, 16 + 2 * j);
        tma_prefetch_3d(&p.wqkv2, 0, m * 64, 32 + 2 * j);
      }
      mbar_expect_tx(bar(B_WPHI), 8192);
      tma_2d(sb + SPARE, &p.wphi, 0, j * 128, bar(B_WPHI));
      PROF_T(32);
    }
    __syncwarp();
  }
  __syncthreads();
  if (warp >= 12) {
    reg_dealloc<40>();
    if (tid == 480) {
      *reinterpret_cast<volatile unsigned*>(smem + MISC) = ticket >> 7;
      mbar_arrive(bar(B_EP));
    }
    unsigned ep1 = 0;
    if (warp & 1) {
      mbar_wait(bar(B_EP), 0);
      ep1 = *reinterpret_cast<volatile unsigned*>(smem + MISC) + 1;
    }
    const int par = (ep1 - 1) & 1;
    if (!real) {
    } else if (warp == 12) {
      if (elect_one()) {
        const int row = m * 128;
        mbar_wait(bar(B_EP), 0);
        unsigned* gp = g_flags + (FL_GRP + (m >> 1)) * 32;
        unsigned gtarget = *reinterpret_cast<volatile unsigned*>(smem + MISC) * (16 * NALIGN);
        auto align = [&](int bit) {
          if (ALIGN_MASK & bit) {
            asm volatile("red.relaxed.gpu.global.add.u32 [%0], 1;" ::"l"(gp) : "memory");
            gtarget += 16;
            uint32_t n = 0, v;
            do {
              asm volatile("ld.relaxed.gpu.global.u32 %0, [%1];" : "=r"(v) : "l"(gp) : "memory");
              if (++n > (1u << 22)) __trap();
            } while ((int)(v - gtarget) < 0);
          }
        };
        uint32_t li = 0, ph = 0;
#pragma unroll 1
        for (int g = 3; g < 32; g++) {
          if (g == 16) { mbar_wait(bar(B_XN), 0); align(1); PROF_T(34); }
          mbar_wait(bar(B_E3 + li), ph);
          mbar_expect_tx(bar(B_F3 + li), 49152);
          tma_2d(sb + RING + li * 49152, g < 16 ? &p.xt : &p.xn, (g & 15) * 64, row, bar(B_F3 + li));
          if (++li == 3) { li = 0; ph ^= 1; }
        }
        align(2);
#pragma unroll 1
        for (int i = 0; i < 16; i++) {
          if (i < 3) {
            mbar_wait(bar(B_E3 + li), ph);
            if (++li == 3) { li = 0; ph ^= 1; }
            if (i == 0) mbar_wait(bar(B_SPARE), 0);
          } else if (i >= 4) {
            mbar_wait(bar(B_E4 + (i & 3)), ((i >> 2) - 1) & 1);
          }
          mbar_expect_tx(bar(B_F4 + (i & 3)), 40960);
          tma_2d(sb + RING + ((i + 3) & 3) * 40960, &p.xn, i * 64, row, bar(B_F4 + (i & 3)));
        }
        align(4);
        li = 0;
        ph = 1;
        uint32_t ps = 4;
        auto step = [&](const CUtensorMap* map, int col) {
          mbar_wait(bar(B_E5 + li), ph);
          mbar_expect_tx(bar(B_F5 + li), 32768);
          tma_2d(sb + RING + ps * 32768, map, col, row, bar(B_F5 + li));
          if (++li == 5) { li = 0; ph ^= 1; }
          if (++ps == 5) ps = 0;
        };
#pragma unroll 1
        for (int n = 0; n < 16; n++) {
          if (n < 4) mbar_wait(bar(B_E4 + n), 1);
          step(&p.xn, n * 64);
        }
        align(8);
        mbar_wait(bar(B_HA), 0);
        PROF_T(4);
#pragma unroll 1
        for (int ks = 0; ks < 32; ks++) step(EXP_HMAP, EXP_COL(448 * (ks >> 2) + 64 * (ks & 3)));
        align(16);
        mbar_wait(bar(B_HB), 0);
        PROF_T(5);
#pragma unroll 1
        for (int jj = 0; jj < 8; jj++) {
#pragma unroll 1
          for (int c = 0; c < 3; c++) step(EXP_HMAP, EXP_COL(448 * jj + 256 + 64 * c));
        }
        mbar_wait(bar(B_O), 0);
        align(32);
        PROF_T(6);
#pragma unroll 1
        for (int k = 0; k < 16; k++) step(&p.o, k * 64);
      }
    } else if (warp == 14) {
      if (elect_one()) {
        uint32_t li = 0, ph = 0;
#pragma unroll 1
        for (int g = 3; g < 32; g++) {
          mbar_wait(bar(B_E3 + li), ph);
          const uint32_t b = sb + RING + li * 49152 + 16384 + rank * 16384;
          if (g < 16) tma_3d_mc(b, &p.wqkv2, 0, g * 64, 16 + 16 * rank + 2 * j, bar(B_F3 + li));
          else tma_3d_mc(b, &p.w1x2, 0, (g - 16) * 64, 7 * j + 2 * rank, bar(B_F3 + li));
          if (m >= PF_SPLIT && g == m - PF_SPLIT + 3) {
            tma_prefetch_3d(&p.wqkv2, 0, m * 64, 16 + 2 * j);
            tma_prefetch_3d(&p.wqkv2, 0, m * 64, 32 + 2 * j);
          }
          if (g == 10) {
            tma_prefetch_3d(&p.w1x2, 0, m * 64, 7 * j);
            tma_prefetch_3d(&p.w1x2, 0, m * 64, 7 * j + 2);
          }
          if (g == 18) {
            tma_prefetch_3d(&p.w1x2, 0, m * 64, 7 * j + 4);
            tma_prefetch_3d(&p.w1h, 0, m * 64, 7 * j + 6);
            tma_prefetch_3d(&p.w1h, 0, m * 64 + 32, 7 * j + 6);
          }
          if (g == 26) tma_prefetch_3d(&p.wqkv2, 0, m * 64, 2 * j);
          if (++li == 3) { li = 0; ph ^= 1; }
        }
#pragma unroll 1
        for (int i = 0; i < 16; i++) {
          if (i < 3) {
            mbar_wait(bar(B_E3 + li), ph);
            if (++li == 3) { li = 0; ph ^= 1; }
            if (i == 0) mbar_wait(bar(B_SPARE), 0);
          } else if (i >= 4) {
            mbar_wait(bar(B_E4 + (i & 3)), ((i >> 2) - 1) & 1);
          }
          const uint32_t b = sb + RING + ((i + 3) & 3) * 40960 + 16384 + rank * 4096;
#pragma unroll
          for (int c = 0; c < 3; c++)
            tma_3d_mc(b + c * 8192, &p.w1h, 0, i * 64 + rank * 32, 7 * j + 4 + c, bar(B_F4 + (i & 3)));
          if (i < 4) {
            const int ks = m + 16 * i;
            if (ks < 56) {
              const int col = ks < 32 ? 448 * (ks >> 2) + 64 * (ks & 3) : 448 * ((ks - 32) / 3) + 256 + 64 * ((ks - 32) % 3);
              tma_prefetch_3d(&p.w2, 0, col, 2 * j);
              tma_prefetch_3d(&p.w2, 0, col, 2 * j + 1);
            }
          }
          if (i == 8) { tma_prefetch_3d(&p.wo, 0, m * 64, 2 * j); tma_prefetch_3d(&p.wo, 0, m * 64, 2 * j + 1); }
        }
        li = 0;
        ph = 1;
        uint32_t ps = 4;
        auto step = [&](const CUtensorMap* map, int krow) {
          mbar_wait(bar(B_E5 + li), ph);
          tma_3d_mc(sb + RING + ps * 32768 + 16384 + rank * 8192, map, 0, krow, 2 * j + rank, bar(B_F5 + li));
          if (++li == 5) { li = 0; ph ^= 1; }
          if (++ps == 5) ps = 0;
        };
#pragma unroll 1
        for (int n = 0; n < 16; n++) {
          if (n < 4) mbar_wait(bar(B_E4 + n), 1);
          step(&p.wqkv1, n * 64);
        }
#pragma unroll 1
        for (int ks = 0; ks < 32; ks++) step(EXP_WMAP, EXP_ROW(448 * (ks >> 2) + 64 * (ks & 3)));
#pragma unroll 1
        for (int jj = 0; jj < 8; jj++) {
#pragma unroll 1
          for (int c = 0; c < 3; c++) step(EXP_WMAP, EXP_ROW(448 * jj + 256 + 64 * c));
        }
#pragma unroll 1
        for (int k = 0; k < 16; k++) step(&p.wo, k * 64);
      }
    } else if (warp == 13) {
      if (elect_one()) {
      mbar_wait(bar(B_LND), 0);
      flag_signal(FL_LN + m);
      PROF_T(2);
      mbar_wait_sleep(bar(B_ED), 0);
      bulk_reduce_add_f32(&g_kv[par][j * 4 * 2048], sb + STG + 32768, 32768);
      bulk_reduce_add_f32(&g_z[par][j * 4 * 64], sb + STG, 1024);
      bulk_commit();
      bulk_wait_read();
      for (int i = 0; i < 4; i++) mbar_arrive(bar(B_SE));
      bulk_wait_all();
      flag_signal(FL_KVP + j);
      PROF_T(17);
      mbar_wait_sleep(bar(B_ED), 1);
      mbar_expect_tx(bar(B_QOP), 8192);
      tma_2d(sb + STG + 49152, &p.wphi, 0, j * 128, bar(B_QOP));
      flag_signal(FL_HA + m);
      PROF_T(18);
      mbar_wait_sleep(bar(B_ED), 0);
      tma_prefetch_2d(&p.xt, j * 128, m * 128);
      tma_prefetch_2d(&p.xt, j * 128 + 64, m * 128);
      flag_signal(FL_HB + m);
      PROF_T(20);
      mbar_wait_sleep(bar(B_ED), 1);
      tma_store_2d(&p.o, sb + STG, j * 128, m * 128);
      tma_store_2d(&p.o, sb + STG + 16384, j * 128 + 64, m * 128);
      bulk_commit();
      mbar_expect_tx(bar(B_XT), 32768);
      tma_2d(sb + STG + 32768, &p.xt, j * 128, m * 128, bar(B_XT));
      tma_2d(sb + STG + 49152, &p.xt, j * 128 + 64, m * 128, bar(B_XT));
      bulk_wait_read();
      for (int i = 0; i < 4; i++) mbar_arrive(bar(B_SE));
      bulk_wait_all();
      flag_signal(FL_O + m);
      PROF_T(22);
      }
    } else {
      float4* kz = reinterpret_cast<float4*>(&g_kv[par ^ 1][(j * 16 + m) * 512]);
#pragma unroll
      for (int i = 0; i < 4; i++) kz[i * 32 + lane] = make_float4(0.f, 0.f, 0.f, 0.f);
      if (lane < 4) reinterpret_cast<float4*>(&g_z[par ^ 1][(j * 16 + m) * 16])[lane] = make_float4(0.f, 0.f, 0.f, 0.f);
      uint4* cz = reinterpret_cast<uint4*>(&g_csp[par ^ 1][(j * 16 + m) * 256]);
      cz[lane] = cz[32 + lane] = make_uint4(0, 0, 0, 0);
      if (elect_one()) {
        flag_wait(FL_LN + m, ep1 * 8);
        fence_async();
        mbar_arrive(bar(B_XN));
        mbar_arrive(bar(B_ST));
        PROF_T(3);
        flag_wait(FL_KVP + j, ep1 * 16);
        mbar_arrive(bar(B_KVR));
        PROF_T(19);
        flag_wait(FL_HA + m, ep1 * 8);
        fence_async();
        mbar_arrive(bar(B_HA));
        flag_wait(FL_HB + m, ep1 * 8);
        fence_async();
        mbar_arrive(bar(B_HB));
        flag_wait(FL_O + m, ep1 * 8);
        fence_async();
        mbar_arrive(bar(B_O));
      }
    }
  } else if (warp >= 8) {
    reg_alloc<136>();
    const int t = tid - 256;
    uint4 cw[16];
    kv_colsum_load(cw, p.wqkv + (size_t)m * 64 * (3 * DM) + j * 128);
    ln_rows<2>(xv, xrow, real);
    warp_arrive(bar(B_LND));
    mbar_wait(bar(B_EP), 0);
    const int par = *reinterpret_cast<volatile unsigned*>(smem + MISC) & 1;
    kv_colsum_publish(cw, &g_csp[par][j * 16 * 256], m, real);
    bf16* hrow = g_h + (size_t)m * 128 * FF + 448 * j;
    uint4 bias_v = make_uint4(0, 0, 0, 0);
    if (t < 56) bias_v = __ldg(reinterpret_cast<const uint4*>(p.b1 + 448 * j) + t);
    if (t < 56) reinterpret_cast<uint4*>(smem + BIAS1)[t] = bias_v;
    reinterpret_cast<uint2*>(smem + ONES)[t] = make_uint2(0x3F803F80u, 0x3F803F80u);
    kv_colsum_gather(sb, &g_csp[par][j * 16 * 256], real);
    warp_arrive(bar(B_CSK));
    if (t == 0) PROF_T(33);
    fence_async_smem();
    named_sync(1, 128);
    if (real) mbar_wait_sleep(bar(B_SF), 0);
    if (t == 0) PROF_T(16);
    kv_epilogue(sb, real ? 4 : 2);
    if (t == 0) PROF_T(28);
    __syncwarp();
    if (lane < 2) mbar_arrive_cluster(bar(B_SPARE), lane);
    warp_arrive(bar(B_ED));
#pragma unroll 1
    for (int tile = 0; tile < 2; tile++) {
      if (real) mbar_wait_sleep(bar(B_SF), tile ^ 1);
      if (t == 0) PROF_T(24 + tile);
      gelu_epilogue(sb, real ? 4 - tile : 1, sb + BIAS1 + tile * 512, hrow + tile * 256, real);
      if (t == 0) PROF_T(26 + tile);
      warp_arrive(bar(B_SE));
      warp_arrive(bar(B_ED));
    }
    named_sync(1, 128);
    if (real) mbar_wait_sleep(bar(B_KVR), 0);
    q_operands(sb, &g_kv[par][j * 4 * 2048], &g_z[par][j * 4 * 64]);
    const uint4 b2a = __ldg(reinterpret_cast<const uint4*>(p.b2 + 128 * j + (t & 7) * 8));
    const uint4 b2b = __ldg(reinterpret_cast<const uint4*>(p.b2 + 128 * j + 64 + (t & 7) * 8));
    named_sync(1, 128);
    if (real) mbar_wait_sleep(bar(B_SF), 1);
    if (t == 0) PROF_T(21);
    q_epilogue(sb, real ? 4 : 1);
    if (t == 0) PROF_T(29);
    fence_async_smem();
    named_sync(1, 128);
    warp_arrive(bar(B_ED));
    if (real) mbar_wait_sleep(bar(B_SF), 0);
    gate_epilogue(sb, b2a, b2b);
    warp_arrive(bar(B_G));
    if (t == 0) PROF_T(23);
  } else {
    {
      uint4 x1[1][4] = {{xv[0][0], xv[0][1], xv[0][2], xv[0][3]}};
      ln_rows<1>(x1, xrow, real);
      warp_arrive(bar(B_LND));
    }
    reg_alloc<168>();
    const int wg = __shfl_sync(0xffffffffu, warp >> 2, 0);
    int li = 0;
    uint32_t ph = 0;
    float none[1];
    float2 st0 = make_float2(0.f, 0.f), st1 = st0;
    {
      float accl[64], accr[64];
      mainloop<256, 64, 64, 3, 49152, 0>(accl, accr, real ? 16 : 1, li, ph, sb, wg, B_F3, B_E3, real, [&](int k) {
        if (k == 13) {
          mbar_wait(bar(B_ST), 0);
          const int row = m * 128 + (threadIdx.x & 127) / 32 * 16 + (threadIdx.x >> 7) * 64 + ((threadIdx.x & 31) >> 2);
          st0 = __ldcg(g_stats + row);
          st1 = __ldcg(g_stats + row + 8);
        }
      });
      if (tid == 0) PROF_T(8);
      if (real) mbar_wait(bar(B_CSK), 0);
      normalize_acc(accr, sb + CSKV + 512, st0, st1);
      dump_v(accr, sb, wg);
      normalize_acc(accl, sb + CSKV, st0, st1);
      if (real) mbar_wait(bar(B_WPHI), 0);
      float pk[64];
      project_acc(accl, pk, sb + SPARE);
      dump_part<128, 0>(pk, sb, wg);
      dump_done(sb);
    }
    {
      float accl[64], accr[64];
      mainloop<256, 64, 64, 3, 49152, 0>(accl, accr, real ? 16 : 1, li, ph, sb, wg, B_F3, B_E3, real);
      if (tid == 0) PROF_T(9);
      if (real) mbar_wait(bar(B_SE), 0);
      dump_part<128, 16>(accr, sb, wg);
      dump_part<128, 0>(accl, sb, wg);
      dump_done(sb);
    }
    {
      float acc[96];
      li = 0; ph = 0;
      mainloop<192, 96, 1, 4, 40960, 3>(acc, none, real ? 16 : 1, li, ph, sb, wg, B_F4, B_E4, real);
      if (tid == 0) PROF_T(10);
      if (real) mbar_wait(bar(B_SE), 1);
      dump_part<192, 0>(acc, sb, wg);
      dump_done(sb);
    }
    li = 0; ph = 0;
    {
      float acc[64];
      mainloop<128, 64, 1, 5, 32768, 4>(acc, none, real ? 16 : 1, li, ph, sb, wg, B_F5, B_E5, real);
      if (tid == 0) PROF_T(11);
      if (real) mbar_wait(bar(B_QOP), 0);
      float pq[64];
      project_acc(acc, pq, sb + STG + 49152);
      if (real) mbar_wait(bar(B_SE), 0);
      dump_part<128, 0>(pq, sb, wg);
      dump_done(sb);
    }
    {
      float acc[64];
      mainloop<128, 64, 1, 5, 32768, 4>(acc, none, real ? 56 : 1, li, ph, sb, wg, B_F5, B_E5, real);
      if (tid == 0) PROF_T(12);
      if (real) mbar_wait(bar(B_SE), 1);
      dump_part<128, 0>(acc, sb, wg);
      dump_done(sb);
    }
    float acc[64];
    mainloop<128, 64, 1, 5, 32768, 4>(acc, none, real ? 16 : 1, li, ph, sb, wg, B_F5, B_E5, real);
    if (tid == 0) PROF_T(13);
    if (real) mbar_wait(bar(B_G), 0);
    if (real) mbar_wait(bar(B_XT), 0);
    {
      const int w = warp & 3;
      const int row = wg * 64 + w * 16 + ((lane >> 3) & 1) * 8 + (lane & 7);
      const int hi = lane >> 4;
#pragma unroll
      for (int g = 0; g < 16; g += 2) {
        const uint32_t off = row * 128 + (g >> 3) * 16384 + ((((g + hi) & 7) ^ (lane & 7)) << 4);
        uint32_t g0, g1, g2, g3, x0, x1, x2, x3;
        ldsm4(sb + STG + off, g0, g1, g2, g3);
        ldsm4(sb + STG + 32768 + off, x0, x1, x2, x3);
        x0 = badd2(x0, bmul2(pack2(acc[4 * g], acc[4 * g + 1]), g0));
        x1 = badd2(x1, bmul2(pack2(acc[4 * g + 2], acc[4 * g + 3]), g1));
        x2 = badd2(x2, bmul2(pack2(acc[4 * g + 4], acc[4 * g + 5]), g2));
        x3 = badd2(x3, bmul2(pack2(acc[4 * g + 6], acc[4 * g + 7]), g3));
        stsm4(sb + STG + 32768 + off, x0, x1, x2, x3);
      }
      fence_async_smem();
      if (wg == 0) named_sync(2, 128); else named_sync(3, 128);
      if ((tid & 127) == 0 && real) {
        tma_store_2d(&p.out64, sb + STG + 32768 + wg * 8192, j * 128, m * 128 + wg * 64);
        tma_store_2d(&p.out64, sb + STG + 49152 + wg * 8192, j * 128 + 64, m * 128 + wg * 64);
        bulk_commit();
        bulk_wait_read();
      }
    }
    if (tid == 0) { PROF_T(14); PROF_G(15); }
  }
  __syncwarp();
  if (warp != 12) cluster_wait();
  cluster_arrive();
  cluster_wait();
}

typedef CUresult (*EncodeTiledFn)(CUtensorMap*, CUtensorMapDataType, cuuint32_t, void*, const cuuint64_t*,
                                  const cuuint64_t*, const cuuint32_t*, const cuuint32_t*, CUtensorMapInterleave,
                                  CUtensorMapSwizzle, CUtensorMapL2promotion, CUtensorMapFloatOOBfill);

void encode(EncodeTiledFn fn, CUtensorMap* map, const void* ptr, int rank, const cuuint64_t* dims,
            const cuuint64_t* strides, const cuuint32_t* box, CUtensorMapSwizzle swz) {
  const cuuint32_t es[3] = {1, 1, 1};
  fn(map, CU_TENSOR_MAP_DATA_TYPE_BFLOAT16, rank, const_cast<void*>(ptr), dims, strides, box, es,
     CU_TENSOR_MAP_INTERLEAVE_NONE, swz, CU_TENSOR_MAP_L2_PROMOTION_L2_256B, CU_TENSOR_MAP_FLOAT_OOB_FILL_NONE);
}
void map_act(EncodeTiledFn fn, CUtensorMap* map, const void* ptr, int rows, int cols, int box_rows) {
  const cuuint64_t dims[2] = {(cuuint64_t)cols, (cuuint64_t)rows}, strides[1] = {(cuuint64_t)cols * 2};
  const cuuint32_t box[2] = {64, (cuuint32_t)box_rows};
  encode(fn, map, ptr, 2, dims, strides, box, CU_TENSOR_MAP_SWIZZLE_128B);
}
void map_w(EncodeTiledFn fn, CUtensorMap* map, const void* ptr, int K, int N, int krows, int chunks) {
  const cuuint64_t dims[3] = {64, (cuuint64_t)K, (cuuint64_t)N / 64}, strides[2] = {(cuuint64_t)N * 2, 128};
  const cuuint32_t box[3] = {64, (cuuint32_t)krows, (cuuint32_t)chunks};
  encode(fn, map, ptr, 3, dims, strides, box, CU_TENSOR_MAP_SWIZZLE_128B);
}

}

extern "C" void kernel_launch(void* const* d_in, const int* in_sizes, int n_in, void* d_out, int out_size) {
  (void)in_sizes; (void)n_in; (void)out_size;
  static EncodeTiledFn fn = nullptr;
  static void *xn = nullptr, *h = nullptr, *o = nullptr;
  if (!fn) {
    void* f = nullptr;
    cudaDriverEntryPointQueryResult q;
    cudaGetDriverEntryPoint("cuTensorMapEncodeTiled", &f, cudaEnableDefault, &q);
    fn = (EncodeTiledFn)f;
    cudaGetSymbolAddress(&xn, g_xn);
    cudaGetSymbolAddress(&h, g_h);
    cudaGetSymbolAddress(&o, g_o);
    cudaFuncSetAttribute(hedgehog_mlp_fused, cudaFuncAttributeMaxDynamicSharedMemorySize, SMEM_BYTES);
  }
  Params p;
  map_act(fn, &p.xn, xn, SEQ, DM, 128);
  map_w(fn, &p.wqkv2, d_in[1], DM, 3 * DM, 64, 2);
  map_w(fn, &p.wqkv1, d_in[1], DM, 3 * DM, 64, 1);
  map_w(fn, &p.w1x2, d_in[5], DM, FF, 64, 2);
  map_w(fn, &p.w1h, d_in[5], DM, FF, 32, 1);
  map_act(fn, &p.h, h, SEQ, FF, 128);
  map_act(fn, &p.o, o, SEQ, DM, 128);
  map_w(fn, &p.w2, d_in[7], FF, DM, 64, 1);
  map_w(fn, &p.wo, d_in[3], DM, DM, 64, 1);
  {
    const cuuint64_t dims[2] = {32, 1024}, strides[1] = {64};
    const cuuint32_t box[2] = {32, 128};
    encode(fn, &p.wphi, d_in[2], 2, dims, strides, box, CU_TENSOR_MAP_SWIZZLE_64B);
  }
  map_act(fn, &p.xt, d_in[0], SEQ, DM, 128);
  map_act(fn, &p.out64, d_out, SEQ, DM, 64);
  p.x = (const bf16*)d_in[0];
  p.wqkv = (const bf16*)d_in[1];
  p.b1 = (const bf16*)d_in[6];
  p.b2 = (const bf16*)d_in[8];
  hedgehog_mlp_fused<<<NCTA + NWARM, 512, SMEM_BYTES, cudaStreamPerThread>>>(p);
}
```

```cpp
#include <cuda_runtime.h>
#include <cuda_bf16.h>
#include <cuda.h>
#include <stdint.h>

namespace {

typedef __nv_bfloat16 bf16;
constexpr int SEQ = 2048, DM = 1024, FF = 3584, NH = 32;
constexpr int NCTA = 128;

__device__ __align__(1024) bf16 g_xn[SEQ * DM];
__device__ __align__(1024) float2 g_stats[SEQ];
__device__ __align__(1024) uint32_t g_csp[2][8 * 16 * 256];
__device__ __align__(1024) bf16 g_h[SEQ * FF];
__device__ __align__(1024) bf16 g_o[SEQ * DM];
__device__ __align__(1024) float g_kv[2][NH * 64 * 32];
__device__ __align__(1024) float g_z[2][NH * 64];
constexpr int FL_TICKET = 0, FL_LN = 1, FL_HA = 17, FL_HB = 33, FL_O = 49, FL_KVP = 65, FL_GRP = 73, FL_NUM = 81;
__device__ __align__(1024) unsigned g_flags[FL_NUM * 32];

struct Params {
  CUtensorMap xn, wqkv2, wqkv1, w1x2, w1x1, w1h, h, o, w2, wo, wphi, xt, out64;
  const bf16* x;
  const bf16* wqkv;
  const bf16* b1;
  const bf16* b2;
};

constexpr uint32_t RING = 0;
constexpr uint32_t SPARE = 147456;
constexpr uint32_t STG = 163840;
constexpr uint32_t BARS = 229376;
constexpr uint32_t MISC = BARS + 368;
constexpr uint32_t BIAS1 = BARS + 384;
constexpr uint32_t ONES = BARS + 2048;
constexpr uint32_t SMEM_BYTES = BARS + 3072;
constexpr uint32_t CSKV = SPARE + 8192;
constexpr uint32_t PHI = SPARE;
constexpr int B_F3 = 0, B_E3 = 3, B_F4 = 6, B_E4 = 10, B_F5 = 14, B_E5 = 19, B_EP = 24, B_HA = 25, B_HB = 26,
              B_O = 27, B_SF = 28, B_SE = 29, B_WPHI = 30, B_SPARE = 31, B_QOP = 32, B_XT = 33, B_G = 34,
              B_KVR = 36, B_CSK = 37, B_LND = 38, B_XN = 39, B_ST = 40, B_ED = 41;

__device__ __forceinline__ uint32_t smem_u32(const void* p) { return (uint32_t)__cvta_generic_to_shared(p); }
__device__ __forceinline__ void mbar_init(uint32_t bar, uint32_t cnt) {
  asm volatile("mbarrier.init.shared::cta.b64 [%0], %1;" ::"r"(bar), "r"(cnt) : "memory");
}
__device__ __forceinline__ void mbar_expect_tx(uint32_t bar, uint32_t bytes) {
  asm volatile("mbarrier.arrive.expect_tx.shared::cta.b64 _, [%0], %1;" ::"r"(bar), "r"(bytes) : "memory");
}
__device__ __forceinline__ void mbar_arrive(uint32_t bar) {
  asm volatile("mbarrier.arrive.shared::cta.b64 _, [%0];" ::"r"(bar) : "memory");
}
__device__ __forceinline__ void mbar_arrive_cluster(uint32_t bar, uint32_t cta) {
  asm volatile("{\n.reg .b32 ra;\nmapa.shared::cluster.u32 ra, %0, %1;\n"
               "mbarrier.arrive.shared::cluster.b64 _, [ra];\n}" ::"r"(bar), "r"(cta) : "memory");
}
__device__ __forceinline__ bool mbar_test(uint32_t bar, uint32_t parity) {
  uint32_t ok;
  asm volatile("{\n.reg .pred p;\nmbarrier.test_wait.parity.shared::cta.b64 p, [%1], %2;\nselp.u32 %0, 1, 0, p;\n}"
               : "=r"(ok) : "r"(bar), "r"(parity) : "memory");
  return ok;
}
__device__ __forceinline__ void mbar_wait(uint32_t bar, uint32_t parity) {
  asm volatile("{\n.reg .pred p;\n.reg .u32 n;\nmov.u32 n, 0;\n"
               "WAIT_LOOP:\n"
               "mbarrier.try_wait.parity.shared::cta.b64 p, [%0], %1;\n"
               "@p bra WAIT_DONE;\n"
               "add.u32 n, n, 1;\n"
               "setp.lt.u32 p, n, 4194304;\n"
               "@p bra WAIT_LOOP;\n"
               "trap;\n"
               "WAIT_DONE:\n}" ::"r"(bar), "r"(parity) : "memory");
}
__device__ __forceinline__ void tma_2d(uint32_t dst, const CUtensorMap* m, int x, int y, uint32_t bar) {
  asm volatile("cp.async.bulk.tensor.2d.shared::cluster.global.mbarrier::complete_tx::bytes [%0], [%1, {%3, %4}], [%2];"
               ::"r"(dst), "l"(m), "r"(bar), "r"(x), "r"(y) : "memory");
}
__device__ __forceinline__ void tma_3d_mc(uint32_t dst, const CUtensorMap* m, int x, int y, int z, uint32_t bar) {
  asm volatile("cp.async.bulk.tensor.3d.shared::cluster.global.mbarrier::complete_tx::bytes.multicast::cluster"
               " [%0], [%1, {%3, %4, %5}], [%2], %6;"
               ::"r"(dst), "l"(m), "r"(bar), "r"(x), "r"(y), "r"(z), "h"((uint16_t)3) : "memory");
}
__device__ __forceinline__ void tma_prefetch_3d(const CUtensorMap* m, int x, int y, int z) {
  asm volatile("cp.async.bulk.prefetch.tensor.3d.L2.global.tile [%0, {%1, %2, %3}];"
               ::"l"(m), "r"(x), "r"(y), "r"(z) : "memory");
}
__device__ __forceinline__ void tma_store_2d(const CUtensorMap* m, uint32_t src, int x, int y) {
  asm volatile("cp.async.bulk.tensor.2d.global.shared::cta.bulk_group [%0, {%2, %3}], [%1];"
               ::"l"(m), "r"(src), "r"(x), "r"(y) : "memory");
}
__device__ __forceinline__ void bulk_commit() { asm volatile("cp.async.bulk.commit_group;" ::: "memory"); }
__device__ __forceinline__ void bulk_wait_read() { asm volatile("cp.async.bulk.wait_group.read 0;" ::: "memory"); }
__device__ __forceinline__ void fence_async() { asm volatile("fence.proxy.async;" ::: "memory"); }
__device__ __forceinline__ void fence_async_smem() { asm volatile("fence.proxy.async.shared::cta;" ::: "memory"); }
__device__ __forceinline__ void wg_fence() { asm volatile("wgmma.fence.sync.aligned;" ::: "memory"); }
__device__ __forceinline__ void wg_commit() { asm volatile("wgmma.commit_group.sync.aligned;" ::: "memory"); }
template <int N>
__device__ __forceinline__ void wg_wait() { asm volatile("wgmma.wait_group.sync.aligned %0;" ::"n"(N) : "memory"); }
__device__ __forceinline__ void wg_wait0_after(uint32_t dep) {
  asm volatile("{\n.reg .pred p;\nsetp.eq.u32 p, %0, 0xFFFFFFFF;\n@p trap;\nwgmma.wait_group.sync.aligned 0;\n}" ::"r"(dep) : "memory");
}
template <int R>
__device__ __forceinline__ void reg_alloc() { asm volatile("setmaxnreg.inc.sync.aligned.u32 %0;" ::"n"(R)); }
template <int R>
__device__ __forceinline__ void reg_dealloc() { asm volatile("setmaxnreg.dec.sync.aligned.u32 %0;" ::"n"(R)); }
__device__ __forceinline__ void named_sync(int id, int n) { asm volatile("bar.sync %0, %1;" ::"r"(id), "r"(n) : "memory"); }
__device__ __forceinline__ bool elect_one() {
  uint32_t ok;
  asm volatile("{\n.reg .pred p;\nelect.sync _|p, 0xffffffff;\nselp.u32 %0, 1, 0, p;\n}" : "=r"(ok));
  return ok;
}
__device__ __forceinline__ void cluster_arrive_relaxed() { asm volatile("barrier.cluster.arrive.relaxed.aligned;" ::: "memory"); }
__device__ __forceinline__ void cluster_wait() { asm volatile("barrier.cluster.wait.acquire.aligned;" ::: "memory"); }
template <int N>
__device__ __forceinline__ void fence_regs(float (&d)[N]) {
#pragma unroll
  for (int i = 0; i < N; i++) asm volatile("" : "+f"(d[i])::"memory");
}
__device__ __forceinline__ uint64_t make_desc(uint32_t addr, uint32_t lbo, uint32_t sbo, uint32_t swz) {
  return (uint64_t)((addr & 0x3FFFF) >> 4) | ((uint64_t)(lbo >> 4) << 16) | ((uint64_t)(sbo >> 4) << 32) |
         ((uint64_t)swz << 62);
}
__device__ __forceinline__ uint64_t desc_add(uint64_t d, uint32_t bytes) {
  return (d & 0xFFFFFFFF00000000ull) | (uint32_t)((uint32_t)d + (bytes >> 4));
}
__device__ __forceinline__ void stsm4(uint32_t addr, uint32_t r0, uint32_t r1, uint32_t r2, uint32_t r3) {
  asm volatile("stmatrix.sync.aligned.m8n8.x4.shared.b16 [%0], {%1, %2, %3, %4};"
               ::"r"(addr), "r"(r0), "r"(r1), "r"(r2), "r"(r3) : "memory");
}
__device__ __forceinline__ void ldsm4(uint32_t addr, uint32_t& r0, uint32_t& r1, uint32_t& r2, uint32_t& r3) {
  asm volatile("ldmatrix.sync.aligned.m8n8.x4.shared.b16 {%0, %1, %2, %3}, [%4];"
               : "=r"(r0), "=r"(r1), "=r"(r2), "=r"(r3) : "r"(addr) : "memory");
}
__device__ __forceinline__ float2 lds64f(uint32_t addr) {
  float2 v;
  asm volatile("ld.shared.v2.f32 {%0, %1}, [%2];" : "=f"(v.x), "=f"(v.y) : "r"(addr) : "memory");
  return v;
}
__device__ __forceinline__ uint2 ld_relaxed_v2(const uint32_t* p) {
  uint2 v;
  asm volatile("ld.relaxed.gpu.global.v2.u32 {%0, %1}, [%2];" : "=r"(v.x), "=r"(v.y) : "l"(p) : "memory");
  return v;
}
__device__ __forceinline__ void red_add_v4(float* p, uint4 v) {
  asm volatile("red.relaxed.gpu.global.add.v4.f32 [%0], {%1, %2, %3, %4};"
               ::"l"(p), "f"(__uint_as_float(v.x)), "f"(__uint_as_float(v.y)), "f"(__uint_as_float(v.z)), "f"(__uint_as_float(v.w)) : "memory");
}
__device__ __forceinline__ void red_add_f32(float* p, float v) {
  asm volatile("red.relaxed.gpu.global.add.f32 [%0], %1;" ::"l"(p), "f"(v) : "memory");
}
__device__ __forceinline__ uint4 ldg128(const void* p) {
  uint4 v;
  asm volatile("ld.global.nc.v4.u32 {%0, %1, %2, %3}, [%4];" : "=r"(v.x), "=r"(v.y), "=r"(v.z), "=r"(v.w) : "l"(p) : "memory");
  return v;
}
__device__ __forceinline__ void stg128(void* p, uint4 v) {
  asm volatile("st.global.v4.u32 [%0], {%1, %2, %3, %4};" ::"l"(p), "r"(v.x), "r"(v.y), "r"(v.z), "r"(v.w) : "memory");
}
__device__ __forceinline__ void st_relaxed_v2(uint32_t* p, uint32_t a, uint32_t b) {
  asm volatile("st.relaxed.gpu.global.v2.u32 [%0], {%1, %2};" ::"l"(p), "r"(a), "r"(b) : "memory");
}
__device__ __forceinline__ void sts64f(uint32_t addr, float a, float b) {
  asm volatile("st.shared.v2.f32 [%0], {%1, %2};" ::"r"(addr), "f"(a), "f"(b) : "memory");
}
__device__ __forceinline__ uint4 lds128(uint32_t addr) {
  uint4 v;
  asm volatile("ld.shared.v4.u32 {%0, %1, %2, %3}, [%4];" : "=r"(v.x), "=r"(v.y), "=r"(v.z), "=r"(v.w) : "r"(addr) : "memory");
  return v;
}
__device__ __forceinline__ void sts32(uint32_t addr, uint32_t a) {
  asm volatile("st.shared.u32 [%0], %1;" ::"r"(addr), "r"(a) : "memory");
}
__device__ __forceinline__ void sts128(uint32_t addr, uint4 v) {
  asm volatile("st.shared.v4.u32 [%0], {%1, %2, %3, %4};" ::"r"(addr), "r"(v.x), "r"(v.y), "r"(v.z), "r"(v.w) : "memory");
}
__device__ __forceinline__ uint32_t pack2(float lo, float hi) {
  uint32_t r;
  asm("cvt.rn.bf16x2.f32 %0, %1, %2;" : "=r"(r) : "f"(hi), "f"(lo));
  return r;
}
__device__ __forceinline__ float bf_lo(uint32_t v) { return __uint_as_float(v << 16); }
__device__ __forceinline__ float bf_hi(uint32_t v) { return __uint_as_float(v & 0xFFFF0000u); }
__device__ __forceinline__ float bf_round(float v) { return __bfloat162float(__float2bfloat16_rn(v)); }
__device__ __forceinline__ uint32_t badd2(uint32_t a, uint32_t b) {
  uint32_t r;
  asm("add.rn.bf16x2 %0, %1, %2;" : "=r"(r) : "r"(a), "r"(b));
  return r;
}
__device__ __forceinline__ uint32_t bfma2(uint32_t a, uint32_t b, uint32_t c) {
  uint32_t r;
  asm("fma.rn.bf16x2 %0, %1, %2, %3;" : "=r"(r) : "r"(a), "r"(b), "r"(c));
  return r;
}
__device__ __forceinline__ uint32_t bmul2(uint32_t a, uint32_t b) {
  uint32_t r;
  asm("mul.rn.bf16x2 %0, %1, %2;" : "=r"(r) : "r"(a), "r"(b));
  return r;
}
__device__ __forceinline__ uint32_t bmax2(uint32_t a, uint32_t b) {
  uint32_t r;
  asm("max.bf16x2 %0, %1, %2;" : "=r"(r) : "r"(a), "r"(b));
  return r;
}
__device__ __forceinline__ uint32_t bmin2(uint32_t a, uint32_t b) {
  uint32_t r;
  asm("min.bf16x2 %0, %1, %2;" : "=r"(r) : "r"(a), "r"(b));
  return r;
}
__device__ __forceinline__ float ex2(float v) {
  float r;
  asm("ex2.approx.ftz.f32 %0, %1;" : "=f"(r) : "f"(v));
  return r;
}
__device__ __forceinline__ float rcp(float v) {
  float r;
  asm("rcp.approx.ftz.f32 %0, %1;" : "=f"(r) : "f"(v));
  return r;
}
constexpr float LOG2E = 1.4426950408889634f;
__device__ __forceinline__ float gelu_tanh_x2(float u) {
  constexpr float C0 = 0.7978845608028654f, C1 = C0 * 0.044715f;
  float th;
  asm("tanh.approx.f32 %0, %1;" : "=f"(th) : "f"(u * fmaf(u * u, C1, C0)));
  return fmaf(u, th, u);
}
__device__ __forceinline__ float silu(float u) { return u * rcp(1.0f + ex2(-LOG2E * u)); }

__device__ __forceinline__ unsigned ld_acquire(const unsigned* p) {
  unsigned v;
  asm volatile("ld.acquire.gpu.global.u32 %0, [%1];" : "=r"(v) : "l"(p) : "memory");
  return v;
}
__device__ __forceinline__ void flag_signal(int idx) {
  asm volatile("fence.acq_rel.gpu;\nred.relaxed.gpu.global.add.u32 [%0], 1;" ::"l"(g_flags + idx * 32) : "memory");
}
__device__ __forceinline__ void flag_wait(int idx, unsigned target) {
  const unsigned* p = g_flags + idx * 32;
  uint32_t n = 0;
  while ((int)(ld_acquire(p) - target) < 0) {
    if (++n > (1u << 22)) __trap();
    __nanosleep(32);
  }
}

template <int TA, int TB>
__device__ __forceinline__ void wgmma_n192(float (&d)[96], uint64_t da, uint64_t db, int sd) {
  asm volatile("{\n.reg .pred p;\nsetp.ne.b32 p, %98, 0;\n"
      "wgmma.mma_async.sync.aligned.m64n192k16.f32.bf16.bf16 "
      "{%0, %1, %2, %3, %4, %5, %6, %7, %8, %9, %10, %11, %12, %13, %14, %15, "
      "%16, %17, %18, %19, %20, %21, %22, %23, %24, %25, %26, %27, %28, %29, %30, %31, "
      "%32, %33, %34, %35, %36, %37, %38, %39, %40, %41, %42, %43, %44, %45, %46, %47, "
      "%48, %49, %50, %51, %52, %53, %54, %55, %56, %57, %58, %59, %60, %61, %62, %63, "
      "%64, %65, %66, %67, %68, %69, %70, %71, %72, %73, %74, %75, %76, %77, %78, %79, "
      "%80, %81, %82, %83, %84, %85, %86, %87, %88, %89, %90, %91, %92, %93, %94, %95}, "
      "%96, %97, p, 1, 1, %99, %100;\n}\n"
      : "+f"(d[0]), "+f"(d[1]), "+f"(d[2]), "+f"(d[3]), "+f"(d[4]), "+f"(d[5]), "+f"(d[6]), "+f"(d[7]),
        "+f"(d[8]), "+f"(d[9]), "+f"(d[10]), "+f"(d[11]), "+f"(d[12]), "+f"(d[13]), "+f"(d[14]), "+f"(d[15]),
        "+f"(d[16]), "+f"(d[17]), "+f"(d[18]), "+f"(d[19]), "+f"(d[20]), "+f"(d[21]), "+f"(d[22]), "+f"(d[23]),
        "+f"(d[24]), "+f"(d[25]), "+f"(d[26]), "+f"(d[27]), "+f"(d[28]), "+f"(d[29]), "+f"(d[30]), "+f"(d[31]),
        "+f"(d[32]), "+f"(d[33]), "+f"(d[34]), "+f"(d[35]), "+f"(d[36]), "+f"(d[37]), "+f"(d[38]), "+f"(d[39]),
        "+f"(d[40]), "+f"(d[41]), "+f"(d[42]), "+f"(d[43]), "+f"(d[44]), "+f"(d[45]), "+f"(d[46]), "+f"(d[47]),
        "+f"(d[48]), "+f"(d[49]), "+f"(d[50]), "+f"(d[51]), "+f"(d[52]), "+f"(d[53]), "+f"(d[54]), "+f"(d[55]),
        "+f"(d[56]), "+f"(d[57]), "+f"(d[58]), "+f"(d[59]), "+f"(d[60]), "+f"(d[61]), "+f"(d[62]), "+f"(d[63]),
        "+f"(d[64]), "+f"(d[65]), "+f"(d[66]), "+f"(d[67]), "+f"(d[68]), "+f"(d[69]), "+f"(d[70]), "+f"(d[71]),
        "+f"(d[72]), "+f"(d[73]), "+f"(d[74]), "+f"(d[75]), "+f"(d[76]), "+f"(d[77]), "+f"(d[78]), "+f"(d[79]),
        "+f"(d[80]), "+f"(d[81]), "+f"(d[82]), "+f"(d[83]), "+f"(d[84]), "+f"(d[85]), "+f"(d[86]), "+f"(d[87]),
        "+f"(d[88]), "+f"(d[89]), "+f"(d[90]), "+f"(d[91]), "+f"(d[92]), "+f"(d[93]), "+f"(d[94]), "+f"(d[95])
      : "l"(da), "l"(db), "r"(sd), "n"(TA), "n"(TB));
}

template <int TA, int TB>
__device__ __forceinline__ void wgmma_n128(float (&d)[64], uint64_t da, uint64_t db, int sd) {
  asm volatile("{\n.reg .pred p;\nsetp.ne.b32 p, %66, 0;\n"
      "wgmma.mma_async.sync.aligned.m64n128k16.f32.bf16.bf16 "
      "{%0, %1, %2, %3, %4, %5, %6, %7, %8, %9, %10, %11, %12, %13, %14, %15, "
      "%16, %17, %18, %19, %20, %21, %22, %23, %24, %25, %26, %27, %28, %29, %30, %31, "
      "%32, %33, %34, %35, %36, %37, %38, %39, %40, %41, %42, %43, %44, %45, %46, %47, "
      "%48, %49, %50, %51, %52, %53, %54, %55, %56, %57, %58, %59, %60, %61, %62, %63}, "
      "%64, %65, p, 1, 1, %67, %68;\n}\n"
      : "+f"(d[0]), "+f"(d[1]), "+f"(d[2]), "+f"(d[3]), "+f"(d[4]), "+f"(d[5]), "+f"(d[6]), "+f"(d[7]),
        "+f"(d[8]), "+f"(d[9]), "+f"(d[10]), "+f"(d[11]), "+f"(d[12]), "+f"(d[13]), "+f"(d[14]), "+f"(d[15]),
        "+f"(d[16]), "+f"(d[17]), "+f"(d[18]), "+f"(d[19]), "+f"(d[20]), "+f"(d[21]), "+f"(d[22]), "+f"(d[23]),
        "+f"(d[24]), "+f"(d[25]), "+f"(d[26]), "+f"(d[27]), "+f"(d[28]), "+f"(d[29]), "+f"(d[30]), "+f"(d[31]),
        "+f"(d[32]), "+f"(d[33]), "+f"(d[34]), "+f"(d[35]), "+f"(d[36]), "+f"(d[37]), "+f"(d[38]), "+f"(d[39]),
        "+f"(d[40]), "+f"(d[41]), "+f"(d[42]), "+f"(d[43]), "+f"(d[44]), "+f"(d[45]), "+f"(d[46]), "+f"(d[47]),
        "+f"(d[48]), "+f"(d[49]), "+f"(d[50]), "+f"(d[51]), "+f"(d[52]), "+f"(d[53]), "+f"(d[54]), "+f"(d[55]),
        "+f"(d[56]), "+f"(d[57]), "+f"(d[58]), "+f"(d[59]), "+f"(d[60]), "+f"(d[61]), "+f"(d[62]), "+f"(d[63])
      : "l"(da), "l"(db), "r"(sd), "n"(TA), "n"(TB));
}

template <int TB, int OFF>
__device__ __forceinline__ void wgmma_rs_n32(float (&d)[64], uint32_t a0, uint32_t a1, uint32_t a2, uint32_t a3,
                                            uint64_t db, int sd) {
  asm volatile("{\n.reg .pred p;\nsetp.ne.b32 p, %21, 0;\n"
      "wgmma.mma_async.sync.aligned.m64n32k16.f32.bf16.bf16 "
      "{%0, %1, %2, %3, %4, %5, %6, %7, %8, %9, %10, %11, %12, %13, %14, %15}, "
      "{%16, %17, %18, %19}, %20, p, 1, 1, %22;\n}\n"
      : "+f"(d[OFF + 0]), "+f"(d[OFF + 1]), "+f"(d[OFF + 2]), "+f"(d[OFF + 3]), "+f"(d[OFF + 4]), "+f"(d[OFF + 5]), "+f"(d[OFF + 6]), "+f"(d[OFF + 7]),
        "+f"(d[OFF + 8]), "+f"(d[OFF + 9]), "+f"(d[OFF + 10]), "+f"(d[OFF + 11]), "+f"(d[OFF + 12]), "+f"(d[OFF + 13]), "+f"(d[OFF + 14]), "+f"(d[OFF + 15])
      : "r"(a0), "r"(a1), "r"(a2), "r"(a3), "l"(db), "r"(sd), "n"(TB));
}

template <int TA, int TB>
__device__ __forceinline__ void wgmma_n40(float (&d)[20], uint64_t da, uint64_t db, int sd) {
  asm volatile("{\n.reg .pred p;\nsetp.ne.b32 p, %22, 0;\n"
      "wgmma.mma_async.sync.aligned.m64n40k16.f32.bf16.bf16 "
      "{%0, %1, %2, %3, %4, %5, %6, %7, %8, %9, %10, %11, %12, %13, %14, %15, "
      "%16, %17, %18, %19}, "
      "%20, %21, p, 1, 1, %23, %24;\n}\n"
      : "+f"(d[0]), "+f"(d[1]), "+f"(d[2]), "+f"(d[3]), "+f"(d[4]), "+f"(d[5]), "+f"(d[6]), "+f"(d[7]),
        "+f"(d[8]), "+f"(d[9]), "+f"(d[10]), "+f"(d[11]), "+f"(d[12]), "+f"(d[13]), "+f"(d[14]), "+f"(d[15]),
        "+f"(d[16]), "+f"(d[17]), "+f"(d[18]), "+f"(d[19])
      : "l"(da), "l"(db), "r"(sd), "n"(TA), "n"(TB));
}

template <int TB>
__device__ __forceinline__ void wgmma_rs_n40(float (&d)[20], uint32_t a0, uint32_t a1, uint32_t a2, uint32_t a3,
                                            uint64_t db, int sd) {
  asm volatile("{\n.reg .pred p;\nsetp.ne.b32 p, %25, 0;\n"
      "wgmma.mma_async.sync.aligned.m64n40k16.f32.bf16.bf16 "
      "{%0, %1, %2, %3, %4, %5, %6, %7, %8, %9, %10, %11, %12, %13, %14, %15, "
      "%16, %17, %18, %19}, "
      "{%20, %21, %22, %23}, %24, p, 1, 1, %26;\n}\n"
      : "+f"(d[0]), "+f"(d[1]), "+f"(d[2]), "+f"(d[3]), "+f"(d[4]), "+f"(d[5]), "+f"(d[6]), "+f"(d[7]),
        "+f"(d[8]), "+f"(d[9]), "+f"(d[10]), "+f"(d[11]), "+f"(d[12]), "+f"(d[13]), "+f"(d[14]), "+f"(d[15]),
        "+f"(d[16]), "+f"(d[17]), "+f"(d[18]), "+f"(d[19])
      : "r"(a0), "r"(a1), "r"(a2), "r"(a3), "l"(db), "r"(sd), "n"(TB));
}


__device__ __forceinline__ void release_stage(uint32_t bar, int l, int rank) {
  if (l == 64) mbar_arrive(bar);
  if (l == 96) mbar_arrive_cluster(bar, rank ^ 1);
}
struct NoHook { __device__ __forceinline__ void operator()(int) const {} };
template <int N, int NA, int NB, int NS, int SBYTES, int ROT, bool LAST = false, class Hook = NoHook>
__device__ __forceinline__ void mainloop(float (&acc)[NA], float (&acc2)[NB], int nsteps, int& li, uint32_t& ph,
                                         uint32_t sb, int wg, int bar_full, int bar_empty, bool real, Hook hook = Hook()) {
  const int l = threadIdx.x & 127;
  const uint64_t da_base = make_desc(sb + RING + wg * 8192, 16, 1024, 1);
  const uint64_t db_base = make_desc(sb + RING + 16384, 8192, 1024, 1);
  int prev = 0;
#pragma unroll 1
  for (int k = 0; k < nsteps; k++) {
    bool released = k == 0;
    if (!mbar_test(sb + BARS + 8 * (bar_full + li), ph) && real) {
      if (!released) {
        wg_wait<0>();
        if (!(LAST && k > nsteps - NS)) release_stage(sb + BARS + 8 * (bar_empty + prev), l, blockIdx.x & 1);
        released = true;
      }
      mbar_wait(sb + BARS + 8 * (bar_full + li), ph);
    }
    int ps = li + ROT;
    if (ps >= NS) ps -= NS;
    const uint64_t da0 = desc_add(da_base, ps * SBYTES), db0 = desc_add(db_base, ps * SBYTES);
    wg_fence();
#pragma unroll
    for (int kk = 0; kk < 4; kk++) {
      const uint64_t da = desc_add(da0, kk * 32);
      const uint64_t db = desc_add(db0, kk * 2048);
      if constexpr (N == 256) {
        wgmma_n128<0, 1>(acc, da, db, (k | kk) != 0);
        wgmma_n128<0, 1>(acc2, da, desc_add(db, 16384), (k | kk) != 0);
      }
      if constexpr (N == 192) wgmma_n192<0, 1>(acc, da, db, (k | kk) != 0);
      if constexpr (N == 128) wgmma_n128<0, 1>(acc, da, db, (k | kk) != 0);
    }
    wg_commit();
    if (!released) {
      wg_wait<1>();
      if (!(LAST && k > nsteps - NS)) release_stage(sb + BARS + 8 * (bar_empty + prev), l, blockIdx.x & 1);
    }
    hook(k);
    prev = li;
    if (++li == NS) { li = 0; ph ^= 1; }
  }
  wg_wait<0>();
  if (!LAST) release_stage(sb + BARS + 8 * (bar_empty + prev), l, blockIdx.x & 1);
  fence_regs(acc);
  if constexpr (N == 256) fence_regs(acc2);
}

template <int N, int G0>
__device__ __forceinline__ void dump_part(float (&acc)[N / 2], uint32_t sb, int wg) {
  const int lane = threadIdx.x & 31, w = (threadIdx.x >> 5) & 3;
  const int row = wg * 64 + w * 16 + ((lane >> 3) & 1) * 8 + (lane & 7);
  const uint32_t base = sb + STG + row * 128;
  const int hi = lane >> 4;
#pragma unroll
  for (int g = 0; g < N / 8; g += 2) {
    const int cg = g + hi;
    const uint32_t addr = base + ((G0 + g) >> 3) * 16384 + (((cg & 7) ^ (lane & 7)) << 4);
    stsm4(addr, pack2(acc[4 * g], acc[4 * g + 1]), pack2(acc[4 * g + 2], acc[4 * g + 3]),
          pack2(acc[4 * g + 4], acc[4 * g + 5]), pack2(acc[4 * g + 6], acc[4 * g + 7]));
  }
}
__device__ __forceinline__ void normalize_pack(const float (&acc)[64], uint32_t cs, float2 st0, float2 st1, uint32_t (&o)[32]) {
  const uint32_t a = cs + (threadIdx.x & 3) * 8;
#pragma unroll
  for (int g = 0; g < 16; g++) {
    const float2 c = lds64f(a + g * 32);
    o[2 * g] = pack2(fmaf(acc[4 * g], st0.x, st0.y * c.x), fmaf(acc[4 * g + 1], st0.x, st0.y * c.y));
    o[2 * g + 1] = pack2(fmaf(acc[4 * g + 2], st1.x, st1.y * c.x), fmaf(acc[4 * g + 3], st1.x, st1.y * c.y));
  }
}
__device__ __forceinline__ void project_issue(const uint32_t (&a)[32], float (&acc)[64], uint32_t wphi) {
  const uint64_t db = make_desc(wphi, 512, 512, 2);
  wg_fence();
  wgmma_rs_n32<1, 0>(acc, a[0], a[1], a[2], a[3], db, 0);
  wgmma_rs_n32<1, 16>(acc, a[8], a[9], a[10], a[11], desc_add(db, 2048), 0);
  wgmma_rs_n32<1, 32>(acc, a[16], a[17], a[18], a[19], desc_add(db, 4096), 0);
  wgmma_rs_n32<1, 48>(acc, a[24], a[25], a[26], a[27], desc_add(db, 6144), 0);
  wgmma_rs_n32<1, 0>(acc, a[4], a[5], a[6], a[7], desc_add(db, 1024), 1);
  wgmma_rs_n32<1, 16>(acc, a[12], a[13], a[14], a[15], desc_add(db, 3072), 1);
  wgmma_rs_n32<1, 32>(acc, a[20], a[21], a[22], a[23], desc_add(db, 5120), 1);
  wgmma_rs_n32<1, 48>(acc, a[28], a[29], a[30], a[31], desc_add(db, 7168), 1);
  wg_commit();
}
__device__ __forceinline__ void dump_v(const uint32_t (&v)[32], uint32_t sb, int wg) {
  const int lane = threadIdx.x & 31, w = (threadIdx.x >> 5) & 3;
  const int row = wg * 64 + w * 16 + ((lane >> 3) & 1) * 8 + (lane & 7);
  const uint32_t base = sb + STG + 32768 + row * 64;
  const int hi = lane >> 4, sw = (row >> 1) & 3;
#pragma unroll
  for (int g = 0; g < 16; g += 2) {
    const uint32_t addr = base + (g >> 2) * 8192 + ((((g + hi) & 3) ^ sw) << 4);
    stsm4(addr, v[2 * g], v[2 * g + 1], v[2 * g + 2], v[2 * g + 3]);
  }
}
template <bool ASYNC>
__device__ __forceinline__ void dump_done(uint32_t sb) {
  if (ASYNC) fence_async_smem();
  __syncwarp();
  if ((threadIdx.x & 31) == 0) mbar_arrive(sb + BARS + 8 * B_SF);
}

__device__ __forceinline__ void warp_arrive(uint32_t bar) {
  __syncwarp();
  if ((threadIdx.x & 31) == 0) mbar_arrive(bar);
}

__device__ __forceinline__ void gelu_epilogue(uint32_t sb, int nch, uint32_t bias_s, bf16* dst0, bool real) {
  const int t = threadIdx.x & 127;
  const int cg = t & 7, r0 = t >> 3;
  uint32_t src = sb + STG + r0 * 128 + ((cg ^ (r0 & 7)) << 4);
  bias_s += cg * 16;
  bf16* dst = dst0 + r0 * 64 + cg * 8;
  uint4 v = lds128(src);
#pragma unroll 1
  for (int c = 0; c < nch; c++) {
    const uint4 bias = lds128(bias_s + c * 128);
#pragma unroll 2
    for (int i = 0; i < 8; i++) {
      const uint32_t u0 = badd2(v.x, bias.x), u1 = badd2(v.y, bias.y), u2 = badd2(v.z, bias.z), u3 = badd2(v.w, bias.w);
      src += 2048;
      v = lds128(src);
      uint4 o;
      o.x = pack2(gelu_tanh_x2(bf_lo(u0)), gelu_tanh_x2(bf_hi(u0)));
      o.y = pack2(gelu_tanh_x2(bf_lo(u1)), gelu_tanh_x2(bf_hi(u1)));
      o.z = pack2(gelu_tanh_x2(bf_lo(u2)), gelu_tanh_x2(bf_hi(u2)));
      o.w = pack2(gelu_tanh_x2(bf_lo(u3)), gelu_tanh_x2(bf_hi(u3)));
      *reinterpret_cast<uint4*>(dst + i * 16 * 64 + c * 8192) = o;
    }
  }
}

__device__ __forceinline__ void kv_colsum_load(uint4 (&v)[16], const bf16* wq) {
  const int t = threadIdx.x & 127;
  const int grp = (t & 63) >> 2, sl = t & 3;
  const bf16* p = wq + (size_t)(sl * 16) * (3 * DM) + (t < 64 ? DM : 2 * DM) + grp * 8;
#pragma unroll
  for (int i = 0; i < 16; i++) v[i] = __ldg(reinterpret_cast<const uint4*>(p + (size_t)i * (3 * DM)));
}
__device__ __forceinline__ void kv_colsum_publish(const uint4 (&v)[16], uint32_t* part, int m, bool real) {
  const int t = threadIdx.x & 127;
  {
    const int sl = t & 3;
    float s[8] = {0.f, 0.f, 0.f, 0.f, 0.f, 0.f, 0.f, 0.f};
#pragma unroll
    for (int i = 0; i < 16; i++) {
      s[0] += bf_lo(v[i].x); s[1] += bf_hi(v[i].x); s[2] += bf_lo(v[i].y); s[3] += bf_hi(v[i].y);
      s[4] += bf_lo(v[i].z); s[5] += bf_hi(v[i].z); s[6] += bf_lo(v[i].w); s[7] += bf_hi(v[i].w);
    }
#pragma unroll
    for (int e = 0; e < 8; e++) {
      s[e] += __shfl_xor_sync(0xffffffffu, s[e], 1);
      s[e] += __shfl_xor_sync(0xffffffffu, s[e], 2);
    }
    const float a = sl == 0 ? s[0] : sl == 1 ? s[2] : sl == 2 ? s[4] : s[6];
    const float b = sl == 0 ? s[1] : sl == 1 ? s[3] : sl == 2 ? s[5] : s[7];
    if (real) st_relaxed_v2(part + m * 256 + (t >> 2) * 8 + sl * 2, ~__float_as_uint(a), ~__float_as_uint(b));
  }
}
__device__ __forceinline__ void kv_colsum_gather(uint32_t sb, const uint32_t* part, bool real) {
  const int t = threadIdx.x & 127;
  uint2 u[16];
  for (uint32_t n = 0;; n++) {
#pragma unroll
    for (int i = 0; i < 16; i++) u[i] = ld_relaxed_v2(part + i * 256 + t * 2);
    bool ok = true;
#pragma unroll
    for (int i = 0; i < 16; i++) ok = ok && u[i].x != 0 && u[i].y != 0;
    if (ok || !real) break;
    if (n > (1u << 18)) __trap();
  }
  float a = 0.f, b = 0.f;
#pragma unroll
  for (int i = 0; i < 16; i++) {
    a += __uint_as_float(~u[i].x);
    b += __uint_as_float(~u[i].y);
  }
  sts64f(sb + CSKV + t * 8, a, b);
}

__device__ __forceinline__ void dual_softmax2(const uint32_t (&p)[2][8], uint32_t (&pos)[2][8], uint32_t (&neg)[2][8]) {
  uint32_t mm[4];
#pragma unroll
  for (int q = 0; q < 4; q++) {
    const uint32_t(&v)[8] = p[q >> 1];
    const int r = q & 1;
    const uint32_t mx2 = bmax2(bmax2(v[r], v[2 + r]), bmax2(v[4 + r], v[6 + r]));
    const uint32_t mn2 = bmin2(bmin2(v[r], v[2 + r]), bmin2(v[4 + r], v[6 + r])) ^ 0x80008000u;
    mm[q] = bmax2(__byte_perm(mx2, mn2, 0x5410), __byte_perm(mx2, mn2, 0x7632));
  }
#pragma unroll
  for (int o = 1; o <= 2; o <<= 1) {
    uint32_t t[4];
#pragma unroll
    for (int q = 0; q < 4; q++) t[q] = __shfl_xor_sync(0xffffffffu, mm[q], o);
#pragma unroll
    for (int q = 0; q < 4; q++) mm[q] = bmax2(mm[q], t[q]);
  }
  float ep[4][8], en[4][8], sp[4], sn[4];
#pragma unroll
  for (int q = 0; q < 4; q++) {
    const float mxl = -LOG2E * bf_lo(mm[q]), mnl = -LOG2E * bf_hi(mm[q]);
#pragma unroll
    for (int g = 0; g < 4; g++) {
      const uint32_t w = p[q >> 1][2 * g + (q & 1)];
      const float v0 = bf_lo(w), v1 = bf_hi(w);
      ep[q][2 * g] = ex2(fmaf(v0, LOG2E, mxl));
      ep[q][2 * g + 1] = ex2(fmaf(v1, LOG2E, mxl));
      en[q][2 * g] = ex2(fmaf(v0, -LOG2E, mnl));
      en[q][2 * g + 1] = ex2(fmaf(v1, -LOG2E, mnl));
    }
    sp[q] = ((ep[q][0] + ep[q][1]) + (ep[q][2] + ep[q][3])) + ((ep[q][4] + ep[q][5]) + (ep[q][6] + ep[q][7]));
    sn[q] = ((en[q][0] + en[q][1]) + (en[q][2] + en[q][3])) + ((en[q][4] + en[q][5]) + (en[q][6] + en[q][7]));
  }
#pragma unroll
  for (int o = 1; o <= 2; o <<= 1) {
    float a[4], b[4];
#pragma unroll
    for (int q = 0; q < 4; q++) { a[q] = __shfl_xor_sync(0xffffffffu, sp[q], o); b[q] = __shfl_xor_sync(0xffffffffu, sn[q], o); }
#pragma unroll
    for (int q = 0; q < 4; q++) { sp[q] += a[q]; sn[q] += b[q]; }
  }
#pragma unroll
  for (int q = 0; q < 4; q++) {
    const float ip = rcp(sp[q]), in = rcp(sn[q]);
#pragma unroll
    for (int g = 0; g < 4; g++) {
      pos[q >> 1][2 * g + (q & 1)] = pack2(ep[q][2 * g] * ip, ep[q][2 * g + 1] * ip);
      neg[q >> 1][2 * g + (q & 1)] = pack2(en[q][2 * g] * in, en[q][2 * g + 1] * in);
    }
  }
}

__device__ __forceinline__ void load_logits(uint32_t sb, int h, uint32_t (&p0)[8], uint32_t (&p1)[8]) {
  const int lane = threadIdx.x & 31, w = (threadIdx.x >> 5) & 3;
  const int srow = w * 16 + ((lane >> 3) & 1) * 8 + (lane & 7);
  const int hi = lane >> 4;
  const uint32_t base = sb + STG + (h >> 1) * 16384 + srow * 128;
  const uint32_t o0 = (((h & 1) * 4 + 0 + hi) ^ (lane & 7)) << 4, o1 = (((h & 1) * 4 + 2 + hi) ^ (lane & 7)) << 4;
  ldsm4(base + o0, p0[0], p0[1], p0[2], p0[3]);
  ldsm4(base + o1, p0[4], p0[5], p0[6], p0[7]);
  ldsm4(base + 8192 + o0, p1[0], p1[1], p1[2], p1[3]);
  ldsm4(base + 8192 + o1, p1[4], p1[5], p1[6], p1[7]);
}

__device__ __forceinline__ void kv_reduce_out(const float (&kv)[20], float* kvs, float* zs) {
  const int t = threadIdx.x & 127;
#pragma unroll
  for (int i = 0; i < 4; i++)
    red_add_v4(kvs + (i * 128 + t) * 4, make_uint4(__float_as_uint(kv[4 * i]), __float_as_uint(kv[4 * i + 1]),
                                                    __float_as_uint(kv[4 * i + 2]), __float_as_uint(kv[4 * i + 3])));
  if ((t & 3) == 0) {
    const int f = (t >> 5) * 16 + ((t & 31) >> 2);
    red_add_f32(zs + f, kv[16]);
    red_add_f32(zs + f + 8, kv[18]);
  }
}

template <int SGN>
__device__ __forceinline__ void row_exp(const uint32_t (&p)[16], float m, float (&e)[32]) {
  const float ml = -LOG2E * m;
#pragma unroll
  for (int i = 0; i < 16; i++) {
    e[2 * i] = ex2(fmaf(bf_lo(p[i]), SGN * LOG2E, ml));
    e[2 * i + 1] = ex2(fmaf(bf_hi(p[i]), SGN * LOG2E, ml));
  }
}
__device__ __forceinline__ void row_norm(const float (&e)[32], uint32_t (&o)[16]) {
  float s[4];
#pragma unroll
  for (int q = 0; q < 4; q++)
    s[q] = ((e[8 * q] + e[8 * q + 1]) + (e[8 * q + 2] + e[8 * q + 3])) + ((e[8 * q + 4] + e[8 * q + 5]) + (e[8 * q + 6] + e[8 * q + 7]));
  const float inv = rcp((s[0] + s[1]) + (s[2] + s[3]));
#pragma unroll
  for (int i = 0; i < 16; i++) o[i] = pack2(e[2 * i] * inv, e[2 * i + 1] * inv);
}

__device__ __forceinline__ void kv_epilogue(uint32_t sb, int nheads, float* kvs, float* zs) {
  const int t = threadIdx.x & 127;
  const uint64_t d_phi = make_desc(sb + PHI, 8192, 1024, 1);
  float kv[20];
  const uint32_t phi_row = sb + PHI + t * 128;
#pragma unroll 1
  for (int h = 0; h < nheads; h++) {
    uint32_t pos[16], neg[16], p[16];
    const uint32_t src = sb + STG + (h >> 1) * 16384 + t * 128;
#pragma unroll
    for (int c = 0; c < 4; c++) {
      const uint4 v = lds128(src + ((((h & 1) * 4 + c) ^ (t & 7)) << 4));
      p[4 * c] = v.x; p[4 * c + 1] = v.y; p[4 * c + 2] = v.z; p[4 * c + 3] = v.w;
    }
    uint32_t mx = p[0], mn = p[0];
#pragma unroll
    for (int i = 1; i < 16; i++) { mx = bmax2(mx, p[i]); mn = bmin2(mn, p[i]); }
    float e[32];
    row_exp<1>(p, fmaxf(bf_lo(mx), bf_hi(mx)), e);
    row_norm(e, pos);
    row_exp<-1>(p, -fminf(bf_lo(mn), bf_hi(mn)), e);
    row_norm(e, neg);
    uint32_t dep = 0;
#pragma unroll
    for (int i = 0; i < 16; i++) dep ^= pos[i] ^ neg[i];
    wg_wait0_after(dep);
    fence_regs(kv);
    named_sync(1, 128);
#pragma unroll
    for (int c = 0; c < 4; c++) {
      sts128(phi_row + ((c ^ (t & 7)) << 4), make_uint4(pos[4 * c], pos[4 * c + 1], pos[4 * c + 2], pos[4 * c + 3]));
      sts128(phi_row + (((4 + c) ^ (t & 7)) << 4), make_uint4(neg[4 * c], neg[4 * c + 1], neg[4 * c + 2], neg[4 * c + 3]));
    }
    float prev[20];
#pragma unroll
    for (int i = 0; i < 20; i++) prev[i] = kv[i];
    fence_async_smem();
    named_sync(1, 128);
    wg_fence();
#pragma unroll
    for (int ks = 0; ks < 8; ks++) {
      const uint32_t vs = sb + STG + 32768 + h * 8192 + ks * 1024;
      wgmma_n40<1, 1>(kv, desc_add(d_phi, ks * 2048), make_desc(vs, sb + ONES - vs, 512, 2), ks);
    }
    wg_commit();
    if (h > 0) kv_reduce_out(prev, kvs + (h - 1) * 2048, zs + (h - 1) * 64);
  }
  wg_wait<0>();
  fence_regs(kv);
  kv_reduce_out(kv, kvs + 3 * 2048, zs + 3 * 64);
}

__device__ __forceinline__ void q_operands(uint32_t sb, const float* kvs, const float* zs) {
  const int t = threadIdx.x & 127, lane = t & 31, w = t >> 5;
  float4 v[16];
#pragma unroll
  for (int i = 0; i < 16; i++) v[i] = __ldcg(reinterpret_cast<const float4*>(kvs) + i * 128 + t);
  const float2 z = __ldcg(reinterpret_cast<const float2*>(zs + w * 64) + lane);
  const int f0 = w * 16 + (lane >> 2);
#pragma unroll
  for (int i = 0; i < 16; i++) {
    const int h = i >> 2, g = i & 3;
    const uint32_t a = sb + STG + 32768 + h * 4096 + f0 * 64 + ((g ^ ((f0 >> 1) & 3)) << 4) + (lane & 3) * 4;
    sts32(a, pack2(v[i].x, v[i].y));
    sts32(a + 512, pack2(v[i].z, v[i].w));
  }
  const uint32_t z0 = pack2(z.x, z.x), z1 = pack2(z.y, z.y);
  const uint32_t zo = sb + STG + 57344 + lane * 128 + ((w ^ (lane & 3)) << 4);
  sts128(zo, make_uint4(z0, z0, z0, z0));
  sts128(zo + 64, make_uint4(z1, z1, z1, z1));
  fence_async_smem();
}

__device__ __forceinline__ void q_epilogue(uint32_t sb, int nheads, bf16* o_tile) {
  const int t = threadIdx.x & 127, lane = t & 31, w = t >> 5;
  const int srow = w * 16 + ((lane >> 3) & 1) * 8 + (lane & 7);
  const int hi = lane >> 4;
  const uint32_t img0 = sb + STG + 32768, zt = sb + STG + 57344;
#pragma unroll 1
  for (int h = 0; h < nheads; h++) {
    uint32_t p[2][8], pos[2][8], neg[2][8];
    load_logits(sb, h, p[0], p[1]);
    dual_softmax2(p, pos, neg);
    const uint32_t img = img0 + h * 4096;
    const uint64_t d_kv = make_desc(img, zt + h * 16 - img, 512, 2);
    float num[2][20];
    wg_fence();
#pragma unroll
    for (int half = 0; half < 2; half++) {
#pragma unroll
      for (int ks = 0; ks < 2; ks++)
        wgmma_rs_n40<1>(num[half], pos[half][4 * ks], pos[half][4 * ks + 1], pos[half][4 * ks + 2], pos[half][4 * ks + 3],
                        desc_add(d_kv, ks * 1024), ks);
#pragma unroll
      for (int ks = 0; ks < 2; ks++)
        wgmma_rs_n40<1>(num[half], neg[half][4 * ks], neg[half][4 * ks + 1], neg[half][4 * ks + 2], neg[half][4 * ks + 3],
                        desc_add(d_kv, (2 + ks) * 1024), 1);
    }
    wg_commit();
    wg_wait<0>();
    const uint32_t dst = sb + STG + (h >> 1) * 16384 + srow * 128;
#pragma unroll
    for (int half = 0; half < 2; half++) {
      fence_regs(num[half]);
      const float(&nm)[20] = num[half];
      const float i0 = rcp(bf_round(bf_round(nm[16]) + 1e-6f)), i1 = rcp(bf_round(bf_round(nm[18]) + 1e-6f));
      uint32_t o[8];
#pragma unroll
      for (int g = 0; g < 4; g++) {
        const uint32_t n0 = pack2(nm[4 * g], nm[4 * g + 1]), n1 = pack2(nm[4 * g + 2], nm[4 * g + 3]);
        o[2 * g] = pack2(bf_lo(n0) * i0, bf_hi(n0) * i0);
        o[2 * g + 1] = pack2(bf_lo(n1) * i1, bf_hi(n1) * i1);
      }
      stsm4(dst + half * 8192 + ((((h & 1) * 4 + 0 + hi) ^ (lane & 7)) << 4), o[0], o[1], o[2], o[3]);
      stsm4(dst + half * 8192 + ((((h & 1) * 4 + 2 + hi) ^ (lane & 7)) << 4), o[4], o[5], o[6], o[7]);
    }
    __syncwarp();
#pragma unroll
    for (int i = 0; i < 4; i++) {
      const int row = (i >> 1) * 64 + w * 16 + (i & 1) * 8 + (lane >> 2), c4 = (h & 1) * 4 + (lane & 3);
      const uint4 v = lds128(sb + STG + (h >> 1) * 16384 + row * 128 + ((c4 ^ (row & 7)) << 4));
      stg128(o_tile + (h >> 1) * 8192 + row * 64 + (h & 1) * 32 + (lane & 3) * 8, v);
    }
  }
}

__device__ __forceinline__ void gate_epilogue(uint32_t sb, uint4 bias0, uint4 bias1) {
  const int t = threadIdx.x & 127;
  const int cg = t & 7, r0 = t >> 3;
  uint32_t src = sb + STG + r0 * 128 + ((cg ^ (r0 & 7)) << 4);
#pragma unroll 1
  for (int c = 0; c < 2; c++) {
    const uint4 bias = c == 0 ? bias0 : bias1;
#pragma unroll 2
    for (int i = 0; i < 8; i++) {
      const uint4 v = lds128(src);
      const uint32_t u0 = bfma2(v.x, 0x3F003F00u, bias.x), u1 = bfma2(v.y, 0x3F003F00u, bias.y),
                     u2 = bfma2(v.z, 0x3F003F00u, bias.z), u3 = bfma2(v.w, 0x3F003F00u, bias.w);
      uint4 o;
      o.x = pack2(silu(bf_lo(u0)), silu(bf_hi(u0)));
      o.y = pack2(silu(bf_lo(u1)), silu(bf_hi(u1)));
      o.z = pack2(silu(bf_lo(u2)), silu(bf_hi(u2)));
      o.w = pack2(silu(bf_lo(u3)), silu(bf_hi(u3)));
      sts128(src, o);
      src += 2048;
    }
  }
}

template <int NR>
__device__ __forceinline__ void ln_rows(uint4 (&xv)[NR][4], int xrow, bool real) {
  const int lane = threadIdx.x & 31;
  float s[NR], q[NR];
  auto repack = [&]() {
#pragma unroll
    for (int r = 0; r < NR; r++)
#pragma unroll
      for (int i = 0; i < 4; i++)
        asm volatile("" : "+r"(xv[r][i].x), "+r"(xv[r][i].y), "+r"(xv[r][i].z), "+r"(xv[r][i].w));
  };
#pragma unroll
  for (int r = 0; r < NR; r++) {
    float a = 0.f, b = 0.f;
#pragma unroll
    for (int i = 0; i < 4; i++) {
      a += (bf_lo(xv[r][i].x) + bf_hi(xv[r][i].x)) + (bf_lo(xv[r][i].y) + bf_hi(xv[r][i].y));
      b += (bf_lo(xv[r][i].z) + bf_hi(xv[r][i].z)) + (bf_lo(xv[r][i].w) + bf_hi(xv[r][i].w));
    }
    s[r] = a + b;
  }
#pragma unroll
  for (int o = 16; o > 0; o >>= 1) {
    float t[NR];
#pragma unroll
    for (int r = 0; r < NR; r++) t[r] = __shfl_xor_sync(0xffffffffu, s[r], o);
#pragma unroll
    for (int r = 0; r < NR; r++) s[r] += t[r];
  }
  repack();
#pragma unroll
  for (int r = 0; r < NR; r++) {
    s[r] *= (1.0f / DM);
    float a = 0.f, b = 0.f;
#pragma unroll
    for (int i = 0; i < 4; i++) {
      const uint32_t w[4] = {xv[r][i].x, xv[r][i].y, xv[r][i].z, xv[r][i].w};
#pragma unroll
      for (int e = 0; e < 4; e++) {
        const float d0 = bf_lo(w[e]) - s[r], d1 = bf_hi(w[e]) - s[r];
        a = fmaf(d0, d0, a);
        b = fmaf(d1, d1, b);
      }
    }
    q[r] = a + b;
  }
#pragma unroll
  for (int o = 16; o > 0; o >>= 1) {
    float t[NR];
#pragma unroll
    for (int r = 0; r < NR; r++) t[r] = __shfl_xor_sync(0xffffffffu, q[r], o);
#pragma unroll
    for (int r = 0; r < NR; r++) q[r] += t[r];
  }
  repack();
#pragma unroll
  for (int r = 0; r < NR; r++) {
    const float mb = bf_round(s[r]);
    const float sd = bf_round(sqrtf(bf_round(bf_round(q[r] * (1.0f / DM)) + 1e-5f)));
    const float inv = 1.0f / sd;
    if (lane == 0 && real) g_stats[xrow + r] = make_float2(inv, -mb * inv);
#pragma unroll
    for (int i = 0; i < 4; i++) {
      const uint32_t w[4] = {xv[r][i].x, xv[r][i].y, xv[r][i].z, xv[r][i].w};
      uint32_t o[4];
#pragma unroll
      for (int e = 0; e < 4; e++) {
        const uint32_t d = pack2(bf_lo(w[e]) - mb, bf_hi(w[e]) - mb);
        o[e] = pack2(bf_lo(d) * inv, bf_hi(d) * inv);
      }
      const int grow = xrow + r;
      if (real) *reinterpret_cast<uint4*>(g_xn + ((size_t)((grow >> 7) * 16 + i * 4 + (lane >> 3)) * 128 + (grow & 127)) * 64 + (lane & 7) * 8) =
          make_uint4(o[0], o[1], o[2], o[3]);
    }
  }
}

__global__ void __cluster_dims__(2, 1, 1) __launch_bounds__(512, 1) hedgehog_mlp_fused(const __grid_constant__ Params p) {
  extern __shared__ __align__(1024) uint8_t smem[];
  const uint32_t sb = smem_u32(smem);
  const int tid = threadIdx.x, warp = tid >> 5, lane = tid & 31;
  const int rank = blockIdx.x & 1, cl = blockIdx.x >> 1;
  int unit, j;
  if (cl < 4) { unit = 7; j = 4 + cl; }
  else if (cl < 36) { const int q = (cl - 4) & 7; j = (cl - 4) >> 3; unit = q == 0 ? 0 : (q == 1 ? 7 : q - 1); }
  else { j = 4 + (cl - 36) / 7; unit = (cl - 36) % 7; }
  const int m = unit * 2 + rank;
  const bool real = blockIdx.x < NCTA;
  auto bar = [&](int i) { return sb + BARS + 8 * i; };

  uint4 xv[4][4];
  const int xrow = m * 128 + j * 16 + (warp & 3) * 4;
  if (warp >= 8 && warp < 12) {
#pragma unroll
    for (int rr = 0; rr < 4; rr++)
#pragma unroll
      for (int i = 0; i < 4; i++)
        xv[rr][i] = __ldg(reinterpret_cast<const uint4*>(p.x + (size_t)(xrow + rr) * DM + i * 256 + lane * 8));
  }
  if (warp == 12 && elect_one()) {
    if (sb & 1023) __trap();
    for (int s = 0; s < 3; s++) { mbar_init(bar(B_F3 + s), 1); mbar_init(bar(B_E3 + s), 4); }
    for (int s = 0; s < 4; s++) { mbar_init(bar(B_F4 + s), 1); mbar_init(bar(B_E4 + s), 4); }
    for (int s = 0; s < 5; s++) { mbar_init(bar(B_F5 + s), 1); mbar_init(bar(B_E5 + s), 4); }
    mbar_init(bar(B_SF), 8);
    mbar_init(bar(B_SE), 4);
    for (int s = 0; s < 4; s++) mbar_init(bar(B_ED + s), 4);
    mbar_init(bar(B_WPHI), 1);
    mbar_init(bar(B_SPARE), 8);
    mbar_init(bar(B_QOP), 1);
    mbar_init(bar(B_XT), 4);
    mbar_init(bar(B_G), 4);
    mbar_init(bar(B_KVR), 1);
    mbar_init(bar(B_EP), 1);
    mbar_init(bar(B_CSK), 4);
    mbar_init(bar(B_LND), 4);
    mbar_init(bar(B_XN), 1);
    mbar_init(bar(B_ST), 1);
    mbar_init(bar(B_HA), 1);
    mbar_init(bar(B_HB), 1);
    mbar_init(bar(B_O), 1);
    asm volatile("fence.mbarrier_init.release.cluster;" ::: "memory");
    for (int s = 0; s < 3 && real; s++) {
      mbar_expect_tx(bar(B_F3 + s), 49152);
      tma_2d(sb + RING + s * 49152, &p.xt, s * 64, m * 128, bar(B_F3 + s));
    }
  }
  __syncwarp();
  cluster_arrive_relaxed();
  if (warp == 12) {
    cluster_wait();
    if (real && elect_one()) {
      for (int s = 0; s < 3; s++)
        tma_3d_mc(sb + RING + s * 49152 + 16384 + rank * 16384, &p.wqkv2, 0, s * 64, 16 + 16 * rank + 2 * j, bar(B_F3 + s));
      if (m >= 3 && m < 8) {
        tma_prefetch_3d(&p.wqkv2, 0, m * 64, 16 + 2 * j);
        tma_prefetch_3d(&p.wqkv2, 0, m * 64, 32 + 2 * j);
      }
      mbar_expect_tx(bar(B_WPHI), 8192);
      tma_2d(sb + SPARE, &p.wphi, 0, j * 128, bar(B_WPHI));
    }
    __syncwarp();
  }
  __syncthreads();
  if (warp >= 12) {
    reg_dealloc<40>();
    if (tid == 480) {
      const unsigned ticket = real ? atomicAdd(g_flags + FL_TICKET * 32, 1u) : 0;
      *reinterpret_cast<volatile unsigned*>(smem + MISC) = ticket >> 7;
      mbar_arrive(bar(B_EP));
    }
    unsigned ep1 = 0;
    if (warp & 1) {
      mbar_wait(bar(B_EP), 0);
      ep1 = *reinterpret_cast<volatile unsigned*>(smem + MISC) + 1;
    }
    const int par = (ep1 - 1) & 1;
    if (!real) {
    } else if (warp == 12) {
      if (elect_one()) {
        const int row = m * 128;
        uint32_t li = 0, ph = 0;
#pragma unroll 1
        for (int g = 3; g < 32; g++) {
          if (g == 16) { mbar_wait(bar(B_XN), 0); }
          mbar_wait(bar(B_E3 + li), ph);
          mbar_expect_tx(bar(B_F3 + li), 49152);
          if (g < 16) tma_2d(sb + RING + li * 49152, &p.xt, g * 64, row, bar(B_F3 + li));
          else tma_2d(sb + RING + li * 49152, &p.xn, 0, (m * 16 + g - 16) * 128, bar(B_F3 + li));
          if (++li == 3) { li = 0; ph ^= 1; }
        }
#pragma unroll 1
        for (int i = 0; i < 16; i++) {
          if (i < 3) {
            mbar_wait(bar(B_E3 + li), ph);
            if (++li == 3) { li = 0; ph ^= 1; }
            if (i == 0) mbar_wait(bar(B_SPARE), 0);
          } else if (i >= 4) {
            mbar_wait(bar(B_E4 + (i & 3)), ((i >> 2) - 1) & 1);
          }
          mbar_expect_tx(bar(B_F4 + (i & 3)), 40960);
          tma_2d(sb + RING + ((i + 3) & 3) * 40960, &p.xn, 0, (m * 16 + i) * 128, bar(B_F4 + (i & 3)));
        }
        mbar_wait(bar(B_EP), 0);
        unsigned* gp = g_flags + (FL_GRP + (m >> 1)) * 32;
        unsigned gtarget = *reinterpret_cast<volatile unsigned*>(smem + MISC) * 32;
        auto align = [&]() {
          asm volatile("red.relaxed.gpu.global.add.u32 [%0], 1;" ::"l"(gp) : "memory");
          gtarget += 16;
          uint32_t n = 0, v;
          do {
            asm volatile("ld.relaxed.gpu.global.u32 %0, [%1];" : "=r"(v) : "l"(gp) : "memory");
            if (++n > (1u << 22)) __trap();
          } while ((int)(v - gtarget) < 0);
        };
        align();
        li = 0;
        ph = 1;
        uint32_t ps = 4;
        auto step = [&](const CUtensorMap* map, int tile) {
          mbar_wait(bar(B_E5 + li), ph);
          mbar_expect_tx(bar(B_F5 + li), 32768);
          tma_2d(sb + RING + ps * 32768, map, 0, tile * 128, bar(B_F5 + li));
          if (++li == 5) { li = 0; ph ^= 1; }
          if (++ps == 5) ps = 0;
        };
#pragma unroll 1
        for (int n = 0; n < 16; n++) {
          if (n < 4) mbar_wait(bar(B_E4 + n), 1);
          step(&p.xn, m * 16 + n);
        }
        align();
        mbar_wait(bar(B_HA), 0);
#pragma unroll 1
        for (int ks = 0; ks < 32; ks++) step(&p.h, m * 56 + 7 * (ks >> 2) + (ks & 3));
        mbar_wait(bar(B_HB), 0);
#pragma unroll 1
        for (int jj = 0; jj < 8; jj++) {
#pragma unroll 1
          for (int c = 0; c < 3; c++) step(&p.h, m * 56 + 7 * jj + 4 + c);
        }
        mbar_wait(bar(B_O), 0);
#pragma unroll 1
        for (int k = 0; k < 16; k++) step(&p.o, m * 16 + k);
      }
    } else if (warp == 14) {
      if (elect_one()) {
        uint32_t li = 0, ph = 0;
#pragma unroll 1
        for (int g = 3; g < 32; g++) {
          mbar_wait(bar(B_E3 + li), ph);
          const uint32_t b = sb + RING + li * 49152 + 16384 + rank * 16384;
          if (g < 16) tma_3d_mc(b, &p.wqkv2, 0, g * 64, 16 + 16 * rank + 2 * j, bar(B_F3 + li));
          else tma_3d_mc(b, &p.w1x2, 0, (g - 16) * 64, 7 * j + 2 * rank, bar(B_F3 + li));
          if (m >= 8 && g == m - 8 + 3) {
            tma_prefetch_3d(&p.wqkv2, 0, m * 64, 16 + 2 * j);
            tma_prefetch_3d(&p.wqkv2, 0, m * 64, 32 + 2 * j);
          }
          if (g == 10) {
            tma_prefetch_3d(&p.w1x2, 0, m * 64, 7 * j);
            tma_prefetch_3d(&p.w1x2, 0, m * 64, 7 * j + 2);
          }
          if (g == 18) {
            tma_prefetch_3d(&p.w1x2, 0, m * 64, 7 * j + 4);
            tma_prefetch_3d(&p.w1h, 0, m * 64, 7 * j + 6);
            tma_prefetch_3d(&p.w1h, 0, m * 64 + 32, 7 * j + 6);
          }
          if (g == 26) tma_prefetch_3d(&p.wqkv2, 0, m * 64, 2 * j);
          if (++li == 3) { li = 0; ph ^= 1; }
        }
#pragma unroll 1
        for (int i = 0; i < 16; i++) {
          if (i < 3) {
            mbar_wait(bar(B_E3 + li), ph);
            if (++li == 3) { li = 0; ph ^= 1; }
            if (i == 0) mbar_wait(bar(B_SPARE), 0);
          } else if (i >= 4) {
            mbar_wait(bar(B_E4 + (i & 3)), ((i >> 2) - 1) & 1);
          }
          const uint32_t b = sb + RING + ((i + 3) & 3) * 40960 + 16384;
          tma_3d_mc(b + rank * 8192, &p.w1x1, 0, i * 64, 7 * j + 4 + rank, bar(B_F4 + (i & 3)));
          tma_3d_mc(b + 16384 + rank * 4096, &p.w1h, 0, i * 64 + rank * 32, 7 * j + 6, bar(B_F4 + (i & 3)));
          if (i % 4 == 0 && i / 4 < 4) {
            const int ks = m + 16 * (i / 4);
            if (ks < 56) {
              const int col = ks < 32 ? 448 * (ks >> 2) + 64 * (ks & 3) : 448 * ((ks - 32) / 3) + 256 + 64 * ((ks - 32) % 3);
              tma_prefetch_3d(&p.w2, 0, col, 2 * j);
              tma_prefetch_3d(&p.w2, 0, col, 2 * j + 1);
            }
          }
          if (i == 15) { tma_prefetch_3d(&p.wo, 0, m * 64, 2 * j); tma_prefetch_3d(&p.wo, 0, m * 64, 2 * j + 1); }
        }
        li = 0;
        ph = 1;
        uint32_t ps = 4;
        auto step = [&](const CUtensorMap* map, int krow) {
          mbar_wait(bar(B_E5 + li), ph);
          tma_3d_mc(sb + RING + ps * 32768 + 16384 + rank * 8192, map, 0, krow, 2 * j + rank, bar(B_F5 + li));
          if (++li == 5) { li = 0; ph ^= 1; }
          if (++ps == 5) ps = 0;
        };
#pragma unroll 1
        for (int n = 0; n < 16; n++) {
          if (n < 4) mbar_wait(bar(B_E4 + n), 1);
          step(&p.wqkv1, n * 64);
        }
#pragma unroll 1
        for (int ks = 0; ks < 32; ks++) step(&p.w2, 448 * (ks >> 2) + 64 * (ks & 3));
#pragma unroll 1
        for (int jj = 0; jj < 8; jj++) {
#pragma unroll 1
          for (int c = 0; c < 3; c++) step(&p.w2, 448 * jj + 256 + 64 * c);
        }
#pragma unroll 1
        for (int k = 0; k < 16; k++) step(&p.wo, k * 64);
      }
    } else if (warp == 13) {
      if (elect_one()) {
      mbar_wait(bar(B_LND), 0);
      flag_signal(FL_LN + m);
      mbar_wait(bar(B_ED + 0), 0);
      flag_signal(FL_KVP + j);
      mbar_wait(bar(B_ED + 1), 0);
      mbar_expect_tx(bar(B_QOP), 8192);
      tma_2d(sb + STG + 49152, &p.wphi, 0, j * 128, bar(B_QOP));
      flag_signal(FL_HA + m);
      mbar_wait(bar(B_ED + 2), 0);
      flag_signal(FL_HB + m);
      mbar_wait(bar(B_ED + 3), 0);
      flag_signal(FL_O + m);
      }
    } else {
      float4* kz = reinterpret_cast<float4*>(&g_kv[par ^ 1][(j * 16 + m) * 512]);
#pragma unroll
      for (int i = 0; i < 4; i++) kz[i * 32 + lane] = make_float4(0.f, 0.f, 0.f, 0.f);
      if (lane < 4) reinterpret_cast<float4*>(&g_z[par ^ 1][(j * 16 + m) * 16])[lane] = make_float4(0.f, 0.f, 0.f, 0.f);
      uint4* cz = reinterpret_cast<uint4*>(&g_csp[par ^ 1][(j * 16 + m) * 256]);
      cz[lane] = cz[32 + lane] = make_uint4(0, 0, 0, 0);
      if (elect_one()) {
        flag_wait(FL_LN + m, ep1 * 8);
        fence_async();
        mbar_arrive(bar(B_XN));
        mbar_arrive(bar(B_ST));
        flag_wait(FL_KVP + j, ep1 * 16);
        mbar_arrive(bar(B_KVR));
        flag_wait(FL_HA + m, ep1 * 8);
        fence_async();
        mbar_arrive(bar(B_HA));
        flag_wait(FL_HB + m, ep1 * 8);
        fence_async();
        mbar_arrive(bar(B_HB));
        flag_wait(FL_O + m, ep1 * 8);
        fence_async();
        mbar_arrive(bar(B_O));
      }
    }
  } else if (warp >= 8) {
    reg_alloc<136>();
    const int t = tid - 256;
    uint4 cw[16];
    ln_rows<4>(xv, xrow, real);
    warp_arrive(bar(B_LND));
    kv_colsum_load(cw, p.wqkv + (size_t)m * 64 * (3 * DM) + j * 128);
    mbar_wait(bar(B_EP), 0);
    const int par = *reinterpret_cast<volatile unsigned*>(smem + MISC) & 1;
    kv_colsum_publish(cw, &g_csp[par][j * 16 * 256], m, real);
    bf16* hrow = g_h + (size_t)(m * 56 + 7 * j) * 8192;
    uint4 bias_v = make_uint4(0, 0, 0, 0);
    if (t < 56) bias_v = __ldg(reinterpret_cast<const uint4*>(p.b1 + 448 * j) + t);
    if (t < 56) reinterpret_cast<uint4*>(smem + BIAS1)[t] = bias_v;
    reinterpret_cast<uint2*>(smem + ONES)[t] = make_uint2(0x3F803F80u, 0x3F803F80u);
    kv_colsum_gather(sb, &g_csp[par][j * 16 * 256], real);
    warp_arrive(bar(B_CSK));
    fence_async_smem();
    named_sync(1, 128);
    if (real) mbar_wait(bar(B_SF), 0);
    kv_epilogue(sb, real ? 4 : 2, &g_kv[par][j * 4 * 2048], &g_z[par][j * 4 * 64]);
    named_sync(1, 128);
    warp_arrive(bar(B_SE));
    __syncwarp();
    if (lane < 2) mbar_arrive_cluster(bar(B_SPARE), lane);
    warp_arrive(bar(B_ED + 0));
#pragma unroll 1
    for (int tile = 0; tile < 2; tile++) {
      if (real) mbar_wait(bar(B_SF), tile ^ 1);
      gelu_epilogue(sb, 4 - tile, sb + BIAS1 + tile * 512, hrow + tile * 4 * 8192, real);
      warp_arrive(bar(B_SE));
      warp_arrive(bar(B_ED + 1 + tile));
    }
    named_sync(1, 128);
    if (real) mbar_wait(bar(B_KVR), 0);
    q_operands(sb, &g_kv[par][j * 4 * 2048], &g_z[par][j * 4 * 64]);
    const uint4 b2a = __ldg(reinterpret_cast<const uint4*>(p.b2 + 128 * j + (t & 7) * 8));
    const uint4 b2b = __ldg(reinterpret_cast<const uint4*>(p.b2 + 128 * j + 64 + (t & 7) * 8));
    named_sync(1, 128);
    if (real) mbar_wait(bar(B_SF), 1);
    q_epilogue(sb, real ? 4 : 1, g_o + (size_t)(m * 16 + 2 * j) * 8192);
    {
      const int cg = lane & 7, rr = lane >> 3, w = t >> 5;
      warp_arrive(bar(B_SE));
      warp_arrive(bar(B_ED + 3));
      uint4 xr[16];
#pragma unroll
      for (int i = 0; i < 16; i++) {
        const int row = (i >> 3) * 64 + w * 16 + ((i >> 1) & 3) * 4 + rr, c = i & 1;
        xr[i] = ldg128(p.x + (size_t)(m * 128 + row) * DM + j * 128 + c * 64 + cg * 8);
      }
      named_sync(1, 128);
#pragma unroll
      for (int i = 0; i < 16; i++) {
        const int row = (i >> 3) * 64 + w * 16 + ((i >> 1) & 3) * 4 + rr, c = i & 1;
        sts128(sb + STG + 32768 + c * 16384 + row * 128 + ((cg ^ (row & 7)) << 4), xr[i]);
      }
      warp_arrive(bar(B_XT));
    }
    if (real) mbar_wait(bar(B_SF), 0);
    gate_epilogue(sb, b2a, b2b);
    warp_arrive(bar(B_G));
  } else {
    reg_alloc<168>();
    const int wg = __shfl_sync(0xffffffffu, warp >> 2, 0);
    int li = 0;
    uint32_t ph = 0;
    float none[1];
    float2 st0 = make_float2(0.f, 0.f), st1 = st0;
    {
      float accl[64], accr[64];
      mainloop<256, 64, 64, 3, 49152, 0>(accl, accr, real ? 16 : 1, li, ph, sb, wg, B_F3, B_E3, real, [&](int k) {
        if (k == 13) {
          mbar_wait(bar(B_ST), 0);
          const int row = m * 128 + (threadIdx.x & 127) / 32 * 16 + (threadIdx.x >> 7) * 64 + ((threadIdx.x & 31) >> 2);
          st0 = __ldcg(g_stats + row);
          st1 = __ldcg(g_stats + row + 8);
        }
      });
      if (real) mbar_wait(bar(B_CSK), 0);
      uint32_t vp[32], ka[32];
      normalize_pack(accl, sb + CSKV, st0, st1, ka);
      normalize_pack(accr, sb + CSKV + 512, st0, st1, vp);
      if (real) mbar_wait(bar(B_WPHI), 0);
      float pk[64];
      project_issue(ka, pk, sb + SPARE);
      dump_v(vp, sb, wg);
      wg_wait<0>();
      fence_regs(pk);
      dump_part<128, 0>(pk, sb, wg);
      dump_done<true>(sb);
    }
    {
      float accl[64], accr[64];
      mainloop<256, 64, 64, 3, 49152, 0>(accl, accr, real ? 16 : 1, li, ph, sb, wg, B_F3, B_E3, real);
      if (real) mbar_wait(bar(B_SE), 0);
      dump_part<128, 16>(accr, sb, wg);
      dump_part<128, 0>(accl, sb, wg);
      dump_done<false>(sb);
    }
    {
      float acc[96];
      li = 0; ph = 0;
      mainloop<192, 96, 1, 4, 40960, 3>(acc, none, real ? 16 : 1, li, ph, sb, wg, B_F4, B_E4, real);
      if (real) mbar_wait(bar(B_SE), 1);
      dump_part<192, 0>(acc, sb, wg);
      dump_done<false>(sb);
    }
    li = 0; ph = 0;
    float acc[64];
    {
      float accy[64];
      {
        float pq[64];
        {
          float accq[64];
          mainloop<128, 64, 1, 5, 32768, 4>(accq, none, real ? 16 : 1, li, ph, sb, wg, B_F5, B_E5, real);
          if (real) mbar_wait(bar(B_QOP), 0);
          uint32_t qa[32];
#pragma unroll
          for (int i = 0; i < 32; i++) qa[i] = pack2(accq[2 * i], accq[2 * i + 1]);
          project_issue(qa, pq, sb + STG + 49152);
          wg_wait<0>();
          fence_regs(pq);
        }
        mainloop<128, 64, 1, 5, 32768, 4>(accy, none, real ? 56 : 1, li, ph, sb, wg, B_F5, B_E5, real, [&](int k) {
          if (k == 0) {
            if (real) mbar_wait(bar(B_SE), 0);
            dump_part<128, 0>(pq, sb, wg);
            dump_done<false>(sb);
          }
        });
      }
      mainloop<128, 64, 1, 5, 32768, 4, true>(acc, none, real ? 16 : 1, li, ph, sb, wg, B_F5, B_E5, real, [&](int k) {
        if (k == 0) {
          if (real) mbar_wait(bar(B_SE), 1);
          dump_part<128, 0>(accy, sb, wg);
          dump_done<false>(sb);
        }
      });
    }
    if (real) mbar_wait(bar(B_G), 0);
    if (real) mbar_wait(bar(B_XT), 0);
    {
      const int w = warp & 3;
      const int row = wg * 64 + w * 16 + ((lane >> 3) & 1) * 8 + (lane & 7);
      const int hi = lane >> 4;
#pragma unroll
      for (int c = 0; c < 2; c++) {
#pragma unroll
        for (int g = 8 * c; g < 8 * c + 8; g += 2) {
          const uint32_t off = row * 128 + c * 16384 + ((((g + hi) & 7) ^ (lane & 7)) << 4);
          uint32_t g0, g1, g2, g3, x0, x1, x2, x3;
          ldsm4(sb + STG + off, g0, g1, g2, g3);
          ldsm4(sb + STG + 32768 + off, x0, x1, x2, x3);
          x0 = badd2(x0, bmul2(pack2(acc[4 * g], acc[4 * g + 1]), g0));
          x1 = badd2(x1, bmul2(pack2(acc[4 * g + 2], acc[4 * g + 3]), g1));
          x2 = badd2(x2, bmul2(pack2(acc[4 * g + 4], acc[4 * g + 5]), g2));
          x3 = badd2(x3, bmul2(pack2(acc[4 * g + 6], acc[4 * g + 7]), g3));
          stsm4(sb + STG + 32768 + off, x0, x1, x2, x3);
        }
        fence_async_smem();
        if (wg == 0) named_sync(2, 128); else named_sync(3, 128);
        if ((tid & 127) == 0 && real) {
          tma_store_2d(&p.out64, sb + STG + 32768 + c * 16384 + wg * 8192, j * 128 + c * 64, m * 128 + wg * 64);
          bulk_commit();
        }
      }
      if ((tid & 127) == 0) bulk_wait_read();
    }
  }
}

typedef CUresult (*EncodeTiledFn)(CUtensorMap*, CUtensorMapDataType, cuuint32_t, void*, const cuuint64_t*,
                                  const cuuint64_t*, const cuuint32_t*, const cuuint32_t*, CUtensorMapInterleave,
                                  CUtensorMapSwizzle, CUtensorMapL2promotion, CUtensorMapFloatOOBfill);

void encode(EncodeTiledFn fn, CUtensorMap* map, const void* ptr, int rank, const cuuint64_t* dims,
            const cuuint64_t* strides, const cuuint32_t* box, CUtensorMapSwizzle swz) {
  const cuuint32_t es[3] = {1, 1, 1};
  fn(map, CU_TENSOR_MAP_DATA_TYPE_BFLOAT16, rank, const_cast<void*>(ptr), dims, strides, box, es,
     CU_TENSOR_MAP_INTERLEAVE_NONE, swz, CU_TENSOR_MAP_L2_PROMOTION_L2_128B, CU_TENSOR_MAP_FLOAT_OOB_FILL_NONE);
}
void map_act(EncodeTiledFn fn, CUtensorMap* map, const void* ptr, int rows, int cols, int box_rows) {
  const cuuint64_t dims[2] = {(cuuint64_t)cols, (cuuint64_t)rows}, strides[1] = {(cuuint64_t)cols * 2};
  const cuuint32_t box[2] = {64, (cuuint32_t)box_rows};
  encode(fn, map, ptr, 2, dims, strides, box, CU_TENSOR_MAP_SWIZZLE_128B);
}
void map_w(EncodeTiledFn fn, CUtensorMap* map, const void* ptr, int K, int N, int krows, int chunks) {
  const cuuint64_t dims[3] = {64, (cuuint64_t)K, (cuuint64_t)N / 64}, strides[2] = {(cuuint64_t)N * 2, 128};
  const cuuint32_t box[3] = {64, (cuuint32_t)krows, (cuuint32_t)chunks};
  encode(fn, map, ptr, 3, dims, strides, box, CU_TENSOR_MAP_SWIZZLE_128B);
}

}

extern "C" void kernel_launch(void* const* d_in, const int* in_sizes, int n_in, void* d_out, int out_size) {
  (void)in_sizes; (void)n_in; (void)out_size;
  static EncodeTiledFn fn = nullptr;
  static void *xn = nullptr, *h = nullptr, *o = nullptr;
  if (!fn) {
    void* f = nullptr;
    cudaDriverEntryPointQueryResult q;
    cudaGetDriverEntryPoint("cuTensorMapEncodeTiled", &f, cudaEnableDefault, &q);
    fn = (EncodeTiledFn)f;
    cudaGetSymbolAddress(&xn, g_xn);
    cudaGetSymbolAddress(&h, g_h);
    cudaGetSymbolAddress(&o, g_o);
    cudaFuncSetAttribute(hedgehog_mlp_fused, cudaFuncAttributeMaxDynamicSharedMemorySize, SMEM_BYTES);
  }
  Params p;
  map_act(fn, &p.xn, xn, SEQ * 16, 64, 128);
  map_w(fn, &p.wqkv2, d_in[1], DM, 3 * DM, 64, 2);
  map_w(fn, &p.wqkv1, d_in[1], DM, 3 * DM, 64, 1);
  map_w(fn, &p.w1x2, d_in[5], DM, FF, 64, 2);
  map_w(fn, &p.w1h, d_in[5], DM, FF, 32, 1);
  map_w(fn, &p.w1x1, d_in[5], DM, FF, 64, 1);
  map_act(fn, &p.h, h, SEQ * 56, 64, 128);
  map_act(fn, &p.o, o, SEQ * 16, 64, 128);
  map_w(fn, &p.w2, d_in[7], FF, DM, 64, 1);
  map_w(fn, &p.wo, d_in[3], DM, DM, 64, 1);
  {
    const cuuint64_t dims[2] = {32, 1024}, strides[1] = {64};
    const cuuint32_t box[2] = {32, 128};
    encode(fn, &p.wphi, d_in[2], 2, dims, strides, box, CU_TENSOR_MAP_SWIZZLE_64B);
  }
  map_act(fn, &p.xt, d_in[0], SEQ, DM, 128);
  map_act(fn, &p.out64, d_out, SEQ, DM, 64);
  p.x = (const bf16*)d_in[0];
  p.wqkv = (const bf16*)d_in[1];
  p.b1 = (const bf16*)d_in[6];
  p.b2 = (const bf16*)d_in[8];
  hedgehog_mlp_fused<<<NCTA, 512, SMEM_BYTES, cudaStreamPerThread>>>(p);
}
```
